```python
import torch

def _softmax(x, axis=-1):
    return torch.softmax(x, dim=axis)
def _gelu(x):
    return torch.nn.functional.gelu(x, approximate="tanh")
def _silu(x):
    return torch.nn.functional.silu(x)
def _sigmoid(x):
    return torch.sigmoid(x)
def _layernorm(x, axis=-1, eps=1e-5):
    m = x.mean(dim=axis, keepdim=True)
    v = x.var(dim=axis, keepdim=True, unbiased=False)
    return (x - m) / torch.sqrt(v + eps)
def _scatter_add(tgt, idx, src, axis=0):
    return tgt.clone().index_add_(axis, idx, src)
def _segment_sum(src, seg, n):
    out = torch.zeros((n,) + src.shape[1:], dtype=src.dtype)
    return out.index_add_(0, seg, src)
def _pad(x, pw):
    flat = tuple(v for pair in reversed(pw) for v in pair)
    return torch.nn.functional.pad(x, flat)

kernel_name = 'recurrent_scan__mha_block__glu_gated_swiglu__prompt'

def setup_inputs():

    _w = (lambda a: (lambda t: t.to(torch.bfloat16) if t.is_floating_point() else t)(torch.as_tensor(a)))
    def _A_setup():
        B, S, D, H = 1, 2048, 512, 32
        return {
            "x": _w((lambda *s: torch.randn(*s, dtype=torch.bfloat16) * 0.05)(B, S, D)),
            "wqkv": _w((lambda *s: torch.randn(*s, dtype=torch.bfloat16) * 0.2)(D, 3 * D)),
            "wo": _w((lambda *s: torch.randn(*s, dtype=torch.bfloat16) * 0.2)(D, D)),
        }
    _A_in = _A_setup()

    def _B_setup():
        B, S, D, F = 1, 2048, 512, 1792
        return {
            "x": _w((lambda *s: torch.randn(*s, dtype=torch.bfloat16) * 0.05)(B, S, D)),
            "w1": _w((lambda *s: torch.randn(*s, dtype=torch.bfloat16) * 0.1)(D, F) * (2.0 / D) ** 0.5),
            "w3": _w((lambda *s: torch.randn(*s, dtype=torch.bfloat16) * 0.1)(D, F) * (2.0 / D) ** 0.5),
            "w2": _w((lambda *s: torch.randn(*s, dtype=torch.bfloat16) * 0.1)(F, D) * (2.0 / F) ** 0.5),
        }
    _B_in = _B_setup()

    return {
        "A_x": _A_in["x"],
        "A_wqkv": _A_in["wqkv"],
        "A_wo": _A_in["wo"],
        "B_x": _B_in["x"],
        "B_w1": _B_in["w1"],
        "B_w3": _B_in["w3"],
        "B_w2": _B_in["w2"],
    }

def reference(A_x, A_wqkv, A_wo, B_x, B_w1, B_w3, B_w2):
    def _A_ref(x, wqkv, wo):
        B, S, D = x.shape
        H = 32
        Dh = D // H
        qkv = (lambda x, *d: x.permute(*d))((x @ wqkv).reshape(B, S, 3, H, Dh), 2, 0, 3, 1, 4)
        q, k, v = qkv[0], qkv[1], qkv[2]
        scores = torch.einsum("bhqd,bhkd->bhqk", q, k) * (Dh ** -0.5)
        p = _softmax(scores, axis=-1)
        o = torch.einsum("bhqk,bhkd->bhqd", p, v)
        return (lambda x, *d: x.permute(*d))(o, 0, 2, 1, 3).reshape(B, S, D) @ wo

    def _B_ref(x, w1, w3, w2):
        gate = torch.einsum("bsd,df->bsf", x, w1)
        up = torch.einsum("bsd,df->bsf", x, w3)
        h = _silu(gate) * up
        out = torch.einsum("bsf,fd->bsd", h, w2)
        return out

    x = A_x
    xn = _layernorm(x, axis=-1)
    s = _A_ref(xn, A_wqkv, A_wo)
    g = _silu(_B_ref(xn, B_w1, B_w3, B_w2))
    return x + s * g
```

```cpp
#include <cuda_runtime.h>
#include <cuda_bf16.h>
#include <cuda.h>
#include <stdint.h>

namespace {

typedef __nv_bfloat16 bf16;
constexpr int SEQ = 2048, DM = 512, FF = 1792;
constexpr int NTHREADS = 640;
constexpr int NSLOT = 5;
constexpr uint32_t POLYMASK = 0x57;

constexpr uint32_t SM_A     = 0;
constexpr uint32_t SM_RING  = 131072;
constexpr uint32_t SM_ONES  = SM_RING + 81920;
constexpr uint32_t SM_BIAS  = SM_ONES + 512;
constexpr uint32_t SM_MERGE = SM_BIAS + 2048;
constexpr uint32_t SM_RSTD  = SM_MERGE + 12288;
constexpr uint32_t SM_DELTA = SM_RSTD + 512;
constexpr uint32_t SM_BAR   = SM_DELTA + 512;
constexpr uint32_t B_FULL1  = SM_BAR;
constexpr uint32_t B_EMPTY1 = B_FULL1 + 8 * 2 * NSLOT;
constexpr uint32_t B_KV     = B_EMPTY1 + 8 * NSLOT;
constexpr uint32_t B_FULL2  = B_KV + 64;
constexpr uint32_t B_OE     = B_FULL2 + 24;
constexpr uint32_t B_WO     = B_OE + 16;
constexpr uint32_t B_O      = B_WO + 8;
constexpr uint32_t B_EMPTY2 = B_O + 32;
constexpr uint32_t B_OEE    = B_EMPTY2 + 24;
constexpr uint32_t B_ADONE  = B_OEE + 16;
constexpr uint32_t SM_TOTAL = B_ADONE + 8;

__device__ __align__(1024) uint8_t gQ[32 * SEQ * 32];
__device__ __align__(1024) uint8_t gKV[32 * 16 * 8192];
__device__ __align__(1024) uint8_t gH[32 * 28 * 8192];
__device__ __align__(1024) uint8_t gO[32 * 8 * 8192];
__device__ uint32_t gFlag[72 * 32];
constexpr int F_QKV = 0, F_H = 8, F_O = 40;
#define TSTAMP(role, i)

template<int TB, int SD> __device__ __forceinline__ void wg_rs_n24(float* d, const uint32_t* a, uint64_t db) {
  if (SD)
    asm volatile("wgmma.mma_async.sync.aligned.m64n24k16.f32.bf16.bf16 {%0,%1,%2,%3,%4,%5,%6,%7,%8,%9,%10,%11}, {%12,%13,%14,%15}, %16, 1, 1, 1, %17;"
      : "+f"(d[0]),"+f"(d[1]),"+f"(d[2]),"+f"(d[3]),"+f"(d[4]),"+f"(d[5]),"+f"(d[6]),"+f"(d[7]),"+f"(d[8]),"+f"(d[9]),"+f"(d[10]),"+f"(d[11])
      : "r"(a[0]), "r"(a[1]), "r"(a[2]), "r"(a[3]), "l"(db), "n"(TB));
  else
    asm volatile("wgmma.mma_async.sync.aligned.m64n24k16.f32.bf16.bf16 {%0,%1,%2,%3,%4,%5,%6,%7,%8,%9,%10,%11}, {%12,%13,%14,%15}, %16, 0, 1, 1, %17;"
      : "=f"(d[0]),"=f"(d[1]),"=f"(d[2]),"=f"(d[3]),"=f"(d[4]),"=f"(d[5]),"=f"(d[6]),"=f"(d[7]),"=f"(d[8]),"=f"(d[9]),"=f"(d[10]),"=f"(d[11])
      : "r"(a[0]), "r"(a[1]), "r"(a[2]), "r"(a[3]), "l"(db), "n"(TB));
}
template<int TB, int SD> __device__ __forceinline__ void wg_rs_n64(float* d, const uint32_t* a, uint64_t db) {
  if (SD)
    asm volatile("wgmma.mma_async.sync.aligned.m64n64k16.f32.bf16.bf16 {%0,%1,%2,%3,%4,%5,%6,%7,%8,%9,%10,%11,%12,%13,%14,%15,%16,%17,%18,%19,%20,%21,%22,%23,%24,%25,%26,%27,%28,%29,%30,%31}, {%32,%33,%34,%35}, %36, 1, 1, 1, %37;"
      : "+f"(d[0]),"+f"(d[1]),"+f"(d[2]),"+f"(d[3]),"+f"(d[4]),"+f"(d[5]),"+f"(d[6]),"+f"(d[7]),"+f"(d[8]),"+f"(d[9]),"+f"(d[10]),"+f"(d[11]),"+f"(d[12]),"+f"(d[13]),"+f"(d[14]),"+f"(d[15]),"+f"(d[16]),"+f"(d[17]),"+f"(d[18]),"+f"(d[19]),"+f"(d[20]),"+f"(d[21]),"+f"(d[22]),"+f"(d[23]),"+f"(d[24]),"+f"(d[25]),"+f"(d[26]),"+f"(d[27]),"+f"(d[28]),"+f"(d[29]),"+f"(d[30]),"+f"(d[31])
      : "r"(a[0]), "r"(a[1]), "r"(a[2]), "r"(a[3]), "l"(db), "n"(TB));
  else
    asm volatile("wgmma.mma_async.sync.aligned.m64n64k16.f32.bf16.bf16 {%0,%1,%2,%3,%4,%5,%6,%7,%8,%9,%10,%11,%12,%13,%14,%15,%16,%17,%18,%19,%20,%21,%22,%23,%24,%25,%26,%27,%28,%29,%30,%31}, {%32,%33,%34,%35}, %36, 0, 1, 1, %37;"
      : "=f"(d[0]),"=f"(d[1]),"=f"(d[2]),"=f"(d[3]),"=f"(d[4]),"=f"(d[5]),"=f"(d[6]),"=f"(d[7]),"=f"(d[8]),"=f"(d[9]),"=f"(d[10]),"=f"(d[11]),"=f"(d[12]),"=f"(d[13]),"=f"(d[14]),"=f"(d[15]),"=f"(d[16]),"=f"(d[17]),"=f"(d[18]),"=f"(d[19]),"=f"(d[20]),"=f"(d[21]),"=f"(d[22]),"=f"(d[23]),"=f"(d[24]),"=f"(d[25]),"=f"(d[26]),"=f"(d[27]),"=f"(d[28]),"=f"(d[29]),"=f"(d[30]),"=f"(d[31])
      : "r"(a[0]), "r"(a[1]), "r"(a[2]), "r"(a[3]), "l"(db), "n"(TB));
}
template<int TB> __device__ __forceinline__ void wg_ss_n64(float* d, uint64_t da, uint64_t db) {
  asm volatile("wgmma.mma_async.sync.aligned.m64n64k16.f32.bf16.bf16 {%0,%1,%2,%3,%4,%5,%6,%7,%8,%9,%10,%11,%12,%13,%14,%15,%16,%17,%18,%19,%20,%21,%22,%23,%24,%25,%26,%27,%28,%29,%30,%31}, %32, %33, 1, 1, 1, 0, %34;"
    : "+f"(d[0]),"+f"(d[1]),"+f"(d[2]),"+f"(d[3]),"+f"(d[4]),"+f"(d[5]),"+f"(d[6]),"+f"(d[7]),"+f"(d[8]),"+f"(d[9]),"+f"(d[10]),"+f"(d[11]),"+f"(d[12]),"+f"(d[13]),"+f"(d[14]),"+f"(d[15]),"+f"(d[16]),"+f"(d[17]),"+f"(d[18]),"+f"(d[19]),"+f"(d[20]),"+f"(d[21]),"+f"(d[22]),"+f"(d[23]),"+f"(d[24]),"+f"(d[25]),"+f"(d[26]),"+f"(d[27]),"+f"(d[28]),"+f"(d[29]),"+f"(d[30]),"+f"(d[31])
    : "l"(da), "l"(db), "n"(TB));
}
template<int TB> __device__ __forceinline__ void wg_ss_n128(float* d, uint64_t da, uint64_t db) {
  asm volatile("wgmma.mma_async.sync.aligned.m64n128k16.f32.bf16.bf16 {%0,%1,%2,%3,%4,%5,%6,%7,%8,%9,%10,%11,%12,%13,%14,%15,%16,%17,%18,%19,%20,%21,%22,%23,%24,%25,%26,%27,%28,%29,%30,%31,%32,%33,%34,%35,%36,%37,%38,%39,%40,%41,%42,%43,%44,%45,%46,%47,%48,%49,%50,%51,%52,%53,%54,%55,%56,%57,%58,%59,%60,%61,%62,%63}, %64, %65, 1, 1, 1, 0, %66;"
    : "+f"(d[0]),"+f"(d[1]),"+f"(d[2]),"+f"(d[3]),"+f"(d[4]),"+f"(d[5]),"+f"(d[6]),"+f"(d[7]),"+f"(d[8]),"+f"(d[9]),"+f"(d[10]),"+f"(d[11]),"+f"(d[12]),"+f"(d[13]),"+f"(d[14]),"+f"(d[15]),"+f"(d[16]),"+f"(d[17]),"+f"(d[18]),"+f"(d[19]),"+f"(d[20]),"+f"(d[21]),"+f"(d[22]),"+f"(d[23]),"+f"(d[24]),"+f"(d[25]),"+f"(d[26]),"+f"(d[27]),"+f"(d[28]),"+f"(d[29]),"+f"(d[30]),"+f"(d[31]),"+f"(d[32]),"+f"(d[33]),"+f"(d[34]),"+f"(d[35]),"+f"(d[36]),"+f"(d[37]),"+f"(d[38]),"+f"(d[39]),"+f"(d[40]),"+f"(d[41]),"+f"(d[42]),"+f"(d[43]),"+f"(d[44]),"+f"(d[45]),"+f"(d[46]),"+f"(d[47]),"+f"(d[48]),"+f"(d[49]),"+f"(d[50]),"+f"(d[51]),"+f"(d[52]),"+f"(d[53]),"+f"(d[54]),"+f"(d[55]),"+f"(d[56]),"+f"(d[57]),"+f"(d[58]),"+f"(d[59]),"+f"(d[60]),"+f"(d[61]),"+f"(d[62]),"+f"(d[63])
    : "l"(da), "l"(db), "n"(TB));
}

__device__ __forceinline__ void wg_fence() { asm volatile("wgmma.fence.sync.aligned;" ::: "memory"); }
__device__ __forceinline__ void wg_commit() { asm volatile("wgmma.commit_group.sync.aligned;" ::: "memory"); }
template <int N> __device__ __forceinline__ void wg_wait() { asm volatile("wgmma.wait_group.sync.aligned %0;" ::"n"(N) : "memory"); }
template <int N> __device__ __forceinline__ void pin(float* r) {
#pragma unroll
  for (int i = 0; i < N; i++) asm volatile("" : "+f"(r[i])::"memory");
}
template <int N> __device__ __forceinline__ void clear(float* r) {
#pragma unroll
  for (int i = 0; i < N; i++) r[i] = 0.f;
  pin<N>(r);
}
template <int N> __device__ __forceinline__ void pin(uint32_t* r) {
#pragma unroll
  for (int i = 0; i < N; i++) asm volatile("" : "+r"(r[i])::"memory");
}
__device__ __forceinline__ uint64_t mkdesc(uint32_t addr, uint32_t lbo, uint32_t sbo, uint32_t swz) {
  return (uint64_t)((addr & 0x3FFFF) >> 4) | ((uint64_t)(lbo >> 4) << 16) | ((uint64_t)(sbo >> 4) << 32) | ((uint64_t)swz << 62);
}
__device__ __forceinline__ void mbar_init(uint32_t b, int c) { asm volatile("mbarrier.init.shared::cta.b64 [%0], %1;" ::"r"(b), "r"(c) : "memory"); }
__device__ __forceinline__ void mbar_expect(uint32_t b, int n) { asm volatile("mbarrier.arrive.expect_tx.shared::cta.b64 _, [%0], %1;" ::"r"(b), "r"(n) : "memory"); }
__device__ __forceinline__ void mbar_arrive(uint32_t b) { asm volatile("mbarrier.arrive.shared::cta.b64 _, [%0];" ::"r"(b) : "memory"); }
__device__ __forceinline__ bool mbar_try(uint32_t b, uint32_t ph) {
  uint32_t ok;
  asm volatile("{.reg .pred p; mbarrier.try_wait.parity.shared::cta.b64 p, [%1], %2; selp.u32 %0, 1, 0, p;}" : "=r"(ok) : "r"(b), "r"(ph) : "memory");
  return ok;
}
__device__ __forceinline__ void mbar_wait(uint32_t b, uint32_t ph) {
  if (mbar_try(b, ph)) return;
#pragma unroll 1
  for (int i = 0; i < (1 << 24); i++)
    if (mbar_try(b, ph)) return;
  __trap();
}
__device__ __forceinline__ void mbar_wait_sleep(uint32_t b, uint32_t ph, uint32_t ns) {
#pragma unroll 1
  for (int i = 0; i < (1 << 22); i++) {
    if (mbar_try(b, ph)) return;
    __nanosleep(ns);
  }
  __trap();
}
__device__ __forceinline__ void bulk_load(uint32_t dst, const void* src, int bytes, uint32_t bar) {
  asm volatile("cp.async.bulk.shared::cluster.global.mbarrier::complete_tx::bytes [%0], [%1], %2, [%3];" ::"r"(dst), "l"(src), "r"(bytes), "r"(bar) : "memory");
}
__device__ __forceinline__ void tma_load(uint32_t dst, const CUtensorMap* m, int c0, int c1, uint32_t bar) {
  asm volatile("cp.async.bulk.tensor.2d.shared::cluster.global.mbarrier::complete_tx::bytes [%0], [%1, {%2, %3}], [%4];" ::"r"(dst), "l"(m), "r"(c0), "r"(c1), "r"(bar) : "memory");
}
__device__ __forceinline__ void tma_prefetch(const CUtensorMap* m, int c0, int c1) {
  asm volatile("cp.async.bulk.prefetch.tensor.2d.L2.global [%0, {%1, %2}];" ::"l"(m), "r"(c0), "r"(c1) : "memory");
}
__device__ __forceinline__ bool elect() {
  uint32_t r;
  asm volatile("{.reg .pred p; elect.sync _|p, 0xffffffff; selp.u32 %0, 1, 0, p;}" : "=r"(r));
  return r;
}
__device__ __forceinline__ void bar_sync(int id, int n) { asm volatile("bar.sync %0, %1;" ::"r"(id), "r"(n) : "memory"); }
__device__ __forceinline__ void bar_arrive(int id, int n) { asm volatile("bar.arrive %0, %1;" ::"r"(id), "r"(n) : "memory"); }
__device__ __forceinline__ bool bar_or(int id, int n, bool v) {
  uint32_t r;
  asm volatile("{.reg .pred p, q; setp.ne.u32 q, %3, 0; bar.red.or.pred p, %1, %2, q; selp.u32 %0, 1, 0, p;}" : "=r"(r) : "r"(id), "r"(n), "r"((uint32_t)v) : "memory");
  return r;
}
__device__ __forceinline__ void flag_add(int f) { asm volatile("red.release.gpu.global.add.u32 [%0], 1;" ::"l"(gFlag + f * 32) : "memory"); }
__device__ __forceinline__ void flag_wait(int f, uint32_t target, uint32_t ns) {
#pragma unroll 1
  for (int i = 0; i < (1 << 22); i++) {
    uint32_t v;
    asm volatile("ld.acquire.gpu.global.u32 %0, [%1];" : "=r"(v) : "l"(gFlag + f * 32) : "memory");
    if ((int)(v - target) >= 0) { asm volatile("fence.proxy.async.global;" ::: "memory"); return; }
    __nanosleep(ns);
  }
  __trap();
}
__device__ __forceinline__ float ex2(float x) { float y; asm("ex2.approx.ftz.f32 %0, %1;" : "=f"(y) : "f"(x)); return y; }
__device__ __forceinline__ float rcp(float x) { float y; asm("rcp.approx.ftz.f32 %0, %1;" : "=f"(y) : "f"(x)); return y; }
__device__ __forceinline__ uint32_t packbf(float lo, float hi) { uint32_t d; asm("cvt.rn.bf16x2.f32 %0, %1, %2;" : "=r"(d) : "f"(hi), "f"(lo)); return d; }
__device__ __forceinline__ float bfr(float x) { return __bfloat162float(__float2bfloat16(x)); }
__device__ __forceinline__ float bf_lo(uint32_t u) { return __uint_as_float(u << 16); }
__device__ __forceinline__ float bf_hi(uint32_t u) { return __uint_as_float(u & 0xFFFF0000u); }
__device__ __forceinline__ uint32_t hmul(uint32_t a, uint32_t b) { uint32_t d; asm("mul.rn.bf16x2 %0, %1, %2;" : "=r"(d) : "r"(a), "r"(b)); return d; }
__device__ __forceinline__ uint32_t hadd(uint32_t a, uint32_t b) { uint32_t d; asm("add.rn.bf16x2 %0, %1, %2;" : "=r"(d) : "r"(a), "r"(b)); return d; }
__device__ __forceinline__ uint32_t hsub(uint32_t a, uint32_t b) { uint32_t d; asm("sub.rn.bf16x2 %0, %1, %2;" : "=r"(d) : "r"(a), "r"(b)); return d; }
constexpr float LOG2E = 1.4426950408889634f;

__device__ __forceinline__ uint32_t exp_poly(float lo, float hi, uint32_t half2) {
  uint32_t u, mh, p;
  asm("cvt.pack.sat.s16.s32 %0, %1, %2;" : "=r"(u) : "r"(__float_as_uint(hi)), "r"(__float_as_uint(lo)));
  asm("lop3.b32 %0, %1, 0x007F007F, %2, 0xEA;" : "=r"(mh) : "r"(u), "r"(half2));
  asm("fma.rn.bf16x2 %0, %1, %2, %3;" : "=r"(p) : "r"(u), "r"(mh), "r"(u & 0xFF80FF80u));
  return p;
}
__device__ __forceinline__ void softmax64(float* s, uint32_t* p, uint32_t half2) {
  pin<32>(s);
#pragma unroll
  for (int j = 0; j < 8; j++) {
#pragma unroll
    for (int r = 0; r < 2; r++) {
      const float a = s[4 * j + 2 * r], b = s[4 * j + 2 * r + 1];
      p[2 * j + r] = ((POLYMASK >> j) & 1) ? exp_poly(a, b, half2) : packbf(ex2(a), ex2(b));
    }
  }
  pin<16>(p);
}

struct Tile { int kind, c0, c1; };
__device__ __forceinline__ Tile tile_of(int cg, int t) {
  const int c2 = cg >> 1;
  Tile r;
  if (cg & 1) {
    if (t == 0) { r.kind = 1; r.c0 = c2 * 128; r.c1 = r.c0 + 64; }
    else { r.kind = 2; r.c0 = r.c1 = (7 * c2 + 2 + t) * 64; }
  } else {
    if (t < 2) { r.kind = 0; r.c0 = 512 + c2 * 128 + t * 64; r.c1 = r.c0 + 512; }
    else { r.kind = 2; r.c0 = r.c1 = (7 * c2 + t - 2) * 64; }
  }
  return r;
}

__global__ void __launch_bounds__(NTHREADS, 1)
fused_kernel(const __grid_constant__ CUtensorMap mQKV, const __grid_constant__ CUtensorMap mW1, const __grid_constant__ CUtensorMap mW3,
             const __grid_constant__ CUtensorMap mW2, const __grid_constant__ CUtensorMap mWO, const bf16* __restrict__ x, bf16* __restrict__ out,
             uint32_t zero) {
  extern __shared__ __align__(1024) uint8_t smem[];
  const uint32_t sb = (uint32_t)__cvta_generic_to_shared(smem);
  const int tid = threadIdx.x, lane = tid & 31, g = lane >> 2, t = lane & 3;
  const int warp = __shfl_sync(~0u, tid >> 5, 0), wg = warp >> 2, w = warp & 3;
  const int b = blockIdx.x;
  const int rb = b >> 3, cg = b & 7;
  const int head = b & 31, qb = b >> 5;
  const int rEarly = (rb >> 2) * 8 + ((0x3052 >> ((rb & 3) * 4)) & 7), rLate = (rb >> 2) * 8 + ((0x6741 >> ((rb & 3) * 4)) & 7);

  if (wg == 4) {
    asm volatile("setmaxnreg.dec.sync.aligned.u32 32;");
    if (w == 0) {
      uint32_t epoch;
      asm volatile("ld.relaxed.gpu.global.u32 %0, [%1];" : "=r"(epoch) : "l"(gFlag + F_O * 32) : "memory");
      if (lane < 2 * NSLOT) mbar_init(sb + B_FULL1 + 8 * lane, 1);
      if (lane < NSLOT) mbar_init(sb + B_EMPTY1 + 8 * lane, 8);
      if (lane < 24) mbar_init(sb + B_KV + 8 * lane, lane < 18 ? 1 : lane < 23 ? 4 : 12);
      asm volatile("fence.mbarrier_init.release.cluster;" ::: "memory");
      asm volatile("fence.proxy.async.shared::cta;" ::: "memory");
      __syncwarp();
      bar_arrive(1, 544);
      int slot = 0;
      uint32_t ph = 1;
#pragma unroll 1
      for (int tI = 0; tI < 5; tI++) {
        const Tile tl = tile_of(cg, tI);
        const CUtensorMap *m0 = tl.kind == 2 ? &mW1 : &mQKV, *m1 = tl.kind == 2 ? &mW3 : &mQKV;
#pragma unroll 1
        for (int k = 0; k < 8; k++) {
          const uint32_t full = sb + B_FULL1 + 8 * ((tI & 1) * NSLOT + slot), dst = sb + SM_RING + slot * 16384;
          if (tI == 0 && k == NSLOT) {
            const int i = 2 * NSLOT + rb + lane * 16;
            if (i < 80) {
              const Tile tp = tile_of(cg, i >> 4);
              tma_prefetch((i & 1) ? (tp.kind == 2 ? &mW3 : &mQKV) : (tp.kind == 2 ? &mW1 : &mQKV), (i & 1) ? tp.c1 : tp.c0, ((i >> 1) & 7) * 64);
            }
            __syncwarp();
          }
          mbar_wait(sb + B_EMPTY1 + 8 * slot, ph);
          if (elect()) {
            mbar_expect(full, 16384);
            tma_load(dst, m0, tl.c0, k * 64, full);
            tma_load(dst + 8192, m1, tl.c1, k * 64, full);
          }
          if (++slot == NSLOT) { slot = 0; ph ^= 1; }
        }
      }
      epoch = (epoch >> 5) + 1;
      flag_wait(F_QKV + (head >> 2), epoch * 64, 32);
#pragma unroll 1
      for (int j = 0; j < 8; j++) {
        if (j >= 8 - NSLOT) {
          mbar_wait(sb + B_EMPTY1 + 8 * slot, ph);
          if (++slot == NSLOT) { slot = 0; ph ^= 1; }
        }
        if (elect()) {
          mbar_expect(sb + B_KV + 8 * j, 16384);
          bulk_load(sb + SM_A + j * 16384, gKV + (size_t)head * 131072 + j * 16384, 16384, sb + B_KV + 8 * j);
        }
      }
      flag_wait(F_H + rEarly, epoch * 28, 100);
      flag_wait(F_H + rLate, epoch * 28, 100);
      slot = 0; ph = 1;
#pragma unroll 1
      for (int n = 0; n < 31; n++) {
        const uint32_t full = sb + B_FULL2 + 8 * slot, dst = sb + SM_RING + slot * 24576;
        mbar_wait_sleep(sb + B_EMPTY2 + 8 * slot, ph, 100);
        if (n < 28 && elect()) {
          mbar_expect(full, 24576);
          tma_load(dst, &mW2, cg * 64, n * 64, full);
          bulk_load(dst + 8192, gH + (size_t)(rEarly * 28 + n) * 8192, 8192, full);
          bulk_load(dst + 16384, gH + (size_t)(rLate * 28 + n) * 8192, 8192, full);
        }
        if (++slot == 3) { slot = 0; ph ^= 1; }
      }
      if (elect()) {
        mbar_expect(sb + B_WO, 65536);
#pragma unroll 1
        for (int k = 0; k < 8; k++) tma_load(sb + SM_RING + k * 8192, &mWO, cg * 64, k * 64, sb + B_WO);
      }
      flag_wait(F_O + rEarly, epoch * 32, 200);
#pragma unroll 1
      for (int n = 0; n < 8; n++) {
        mbar_wait_sleep(sb + B_OEE + 8 * (n & 1), ((n >> 1) & 1) ^ 1, 100);
        if (elect()) {
          mbar_expect(sb + B_OE + 8 * (n & 1), 8192);
          bulk_load(sb + SM_RING + 65536 + (n & 1) * 8192, gO + (size_t)(rEarly * 8 + n) * 8192, 8192, sb + B_OE + 8 * (n & 1));
        }
      }
      mbar_wait_sleep(sb + B_ADONE, 0, 100);
      flag_wait(F_O + rLate, epoch * 32, 20);
      if (elect()) {
#pragma unroll
        for (int i = 0; i < 4; i++) {
          mbar_expect(sb + B_O + 8 * i, 16384);
          bulk_load(sb + SM_A + i * 16384, gO + (size_t)rLate * 65536 + i * 16384, 16384, sb + B_O + 8 * i);
        }
      }
    } else {
#pragma unroll 1
      for (int i = 0; i < (w == 2 ? 2 : 3); i++) {
        bar_sync(12 + w, 160);
        if (lane == 0) flag_add(F_O + qb * 8 + (((w == 1 ? 0x102 : w == 2 ? 0x43 : 0x765) >> (i * 4)) & 7));
        __syncwarp();
      }
    }
    return;
  }

  TSTAMP(wg, 0);
  uint4 xv[16];
  {
    const uint4* xp = (const uint4*)(x + (size_t)(rb * 128 + warp * 8 + g) * DM);
#pragma unroll
    for (int j = 0; j < 16; j++) xv[j] = __ldg(xp + 4 * (j ^ (g & 1)) + t);
  }
  asm volatile("setmaxnreg.inc.sync.aligned.u32 112;");

  {
    if (tid < 128) ((uint32_t*)(smem + SM_ONES))[tid] = 0x3F803F80u;
    {
      const int n = tid >> 3, k = (tid & 7) * 2;
      const bool poly = (POLYMASK >> (n >> 3)) & 1;
      const float cm = -127.f + 0.5849625f - 0.0020f, chi = bfr(cm), clo = cm - chi, sc = poly ? 0x1p-71f : 0x1p71f;
      float v0 = 0.f, v1 = 0.f;
      if (k == 0) { v0 = sc; v1 = sc; }
      if (k == 2) { v0 = sc; v1 = poly ? 0.f : chi * sc; }
      if (k == 4) { v0 = poly ? 0.f : clo * sc; }
      *(uint32_t*)(smem + SM_BIAS + n * 32 + (((k >> 3) ^ ((n >> 2) & 1)) << 4) + (k & 7) * 2) = packbf(v0, v1);
    }
    float c0[4] = {0.f, 0.f, 0.f, 0.f}, c1[4] = {0.f, 0.f, 0.f, 0.f};
#pragma unroll
    for (int j = 0; j < 16; j++) {
      float* c = (j & 1) ? c1 : c0;
      asm("mma.sync.aligned.m16n8k16.row.col.f32.bf16.bf16.f32 {%0,%1,%2,%3},{%4,%5,%6,%7},{%8,%8},{%0,%1,%2,%3};"
          : "+f"(c[0]), "+f"(c[1]), "+f"(c[2]), "+f"(c[3]) : "r"(xv[j].x), "r"(xv[j].y), "r"(xv[j].z), "r"(xv[j].w), "r"(0x3F803F80u));
    }
    const float mean = ((c0[0] + c0[2]) + (c1[0] + c1[2])) * (1.f / DM);
    const uint32_t m2 = packbf(mean, mean);
    const int row = warp * 8 + g;
    if (t == 0) ((float*)(smem + SM_DELTA))[row] = mean - bf_lo(m2);
#pragma unroll
    for (int j = 0; j < 16; j++) {
      const int c = 4 * (j ^ (g & 1)) + t;
      uint4 d;
      d.x = hsub(xv[j].x, m2); d.y = hsub(xv[j].y, m2); d.z = hsub(xv[j].z, m2); d.w = hsub(xv[j].w, m2);
      *(uint4*)(smem + SM_A + (c >> 3) * 16384 + row * 128 + (((c & 7) ^ g) << 4)) = d;
    }
    asm volatile("fence.proxy.async.shared::cta;" ::: "memory");
    bar_sync(1, 544);
  }
  TSTAMP(wg, 1);
  const int pair = wg >> 1, half = wg & 1;
  if (pair == 1) {
#pragma unroll 1
    for (int rr = 0; rr < 2; rr++) {
      const int row = (warp - 8) * 16 + rr * 8 + g;
      float s0 = 0.f, s1 = 0.f, s2 = 0.f, s3 = 0.f;
#pragma unroll 4
      for (int j = 0; j < 16; j++) {
        const int c = 4 * (j ^ (g & 1)) + t;
        const uint4 d = *(const uint4*)(smem + SM_A + (c >> 3) * 16384 + row * 128 + (((c & 7) ^ g) << 4));
        float a;
        a = bf_lo(d.x); s0 = fmaf(a, a, s0); a = bf_hi(d.x); s1 = fmaf(a, a, s1);
        a = bf_lo(d.y); s2 = fmaf(a, a, s2); a = bf_hi(d.y); s3 = fmaf(a, a, s3);
        a = bf_lo(d.z); s0 = fmaf(a, a, s0); a = bf_hi(d.z); s1 = fmaf(a, a, s1);
        a = bf_lo(d.w); s2 = fmaf(a, a, s2); a = bf_hi(d.w); s3 = fmaf(a, a, s3);
      }
      float s = (s0 + s1) + (s2 + s3);
      s += __shfl_xor_sync(~0u, s, 1);
      s += __shfl_xor_sync(~0u, s, 2);
      const float dl = ((const float*)(smem + SM_DELTA))[row];
      const float var = fmaxf(s * (1.f / DM) - dl * dl, 0.f);
      if (t == 0) ((float*)(smem + SM_RSTD))[row] = 1.f / bfr(sqrtf(bfr(bfr(var) + 1e-5f)));
    }
    bar_arrive(2, 512);
    bar_sync(3, 256);
  }

  {
    uint32_t par = 0;
    const uint64_t dA0 = mkdesc(sb + SM_A + half * 8192, 16, 1024, 1), dB0 = mkdesc(sb + SM_RING, 8192, 1024, 1);
#pragma unroll 1
    for (int tI = pair; tI < 5; tI += 2) {
      float acc[64];
      clear<64>(acc);
      int slot = (tI * 8) % NSLOT, prev = 0;
#pragma unroll 1
      for (int k = 0; k < 8; k++) {
        mbar_wait(sb + B_FULL1 + 8 * (pair * NSLOT + slot), (par >> slot) & 1);
        par ^= 1u << slot;
        const uint64_t dA = dA0 + k * 1024, dB = dB0 + slot * 1024;
        wg_fence();
        wg_ss_n128<1>(acc, dA, dB);
        wg_ss_n128<1>(acc, dA + 2, dB + 128);
        wg_ss_n128<1>(acc, dA + 4, dB + 256);
        wg_ss_n128<1>(acc, dA + 6, dB + 384);
        wg_commit();
        if (k > 0) {
          wg_wait<1>();
          if (lane == 0) mbar_arrive(sb + B_EMPTY1 + 8 * prev);
        }
        prev = slot;
        if (++slot == NSLOT) slot = 0;
      }
      wg_wait<0>();
      if (lane == 0) mbar_arrive(sb + B_EMPTY1 + 8 * prev);
      pin<64>(acc);
      TSTAMP(wg, 2 + (tI >> 1) * 2);
      if (tI == 0) bar_sync(2, 512);
      const Tile tl = tile_of(cg, tI);
      const int lrow = half * 64 + w * 16 + g;
      const float r0 = ((const float*)(smem + SM_RSTD))[lrow], r1 = ((const float*)(smem + SM_RSTD))[lrow + 8];
      if (tl.kind == 2) {
        uint32_t* hp = (uint32_t*)(gH + (size_t)((rb * 2 + half) * 28 + (tl.c0 >> 6)) * 8192 + w * 256) + lane;
#pragma unroll
        for (int j = 0; j < 8; j++) {
#pragma unroll
          for (int r = 0; r < 2; r++) {
            const float rs = r ? r1 : r0, e = -LOG2E * rs, q = rs * rs;
            const float g0 = acc[4 * j + 2 * r], g1 = acc[4 * j + 2 * r + 1];
            const float h0 = (g0 * q) * acc[32 + 4 * j + 2 * r] * rcp(1.f + ex2(g0 * e));
            const float h1 = (g1 * q) * acc[33 + 4 * j + 2 * r] * rcp(1.f + ex2(g1 * e));
            hp[j * 256 + r * 32] = packbf(h0, h1);
          }
        }
        bar_sync(4 + wg, 128);
        if ((tid & 127) == 0) flag_add(F_H + rb * 2 + half);
      } else {
        const int hg = (tl.c0 >> 6) & 7;
#pragma unroll
        for (int u = 0; u < 2; u++) {
#pragma unroll
          for (int r = 0; r < 2; r++) {
            float sc = r ? r1 : r0;
            uint8_t* p;
            size_t hs;
            if (tl.kind == 1) {
              sc *= 0.25f * LOG2E * 0x1p-71f;
              p = gQ + (size_t)(hg + u) * 4 * 65536 + (size_t)(rb * 128 + lrow + r * 8) * 32 + t * 8;
              hs = 65536;
            } else {
              if (u == 0) sc *= ((POLYMASK >> (2 * w + r)) & 1) ? 0x1p-71f : 0x1p71f;
              p = gKV + (size_t)hg * 4 * 131072 + rb * 8192 + u * 4096 + (lrow + r * 8) * 32 + ((t * 8) ^ ((g & 4) << 2));
              hs = 131072;
            }
#pragma unroll
            for (int hh = 0; hh < 4; hh++) {
              const float* a = acc + u * 32 + hh * 8 + 2 * r;
              *(uint2*)(p + hh * hs) = make_uint2(packbf(a[0] * sc, a[1] * sc), packbf(a[4] * sc, a[5] * sc));
            }
          }
        }
        bar_sync(4 + wg, 128);
        if ((tid & 127) == 0) {
          flag_add(F_QKV + hg);
          if (tl.kind == 1) flag_add(F_QKV + hg + 1);
        }
      }
      TSTAMP(wg, 3 + (tI >> 1) * 2);
    }
  }

  if (wg < 3) {
    constexpr uint64_t VS = (uint64_t)(32 - (32LL << 16));
    const uint32_t half2 = 0x3F003F00u + zero;
    const uint64_t dBias = mkdesc(sb + SM_BIAS, 16, 256, 3);
    const int nseg = wg == 1 ? 4 : 3;
    for (int j = 0; j < 8; j++) mbar_wait(sb + B_KV + 8 * j, 0);
    TSTAMP(wg, 8);
    bool exact = false;
#pragma unroll 1
    for (int seg = 0; seg < nseg; seg++) {
      int rbl, c0 = 0, c1 = 16, mode = 0;
      if (wg == 1) { rbl = (0x4352 >> (seg * 4)) & 7; if (seg < 2) { c0 = 11; mode = 1; } }
      else { rbl = ((wg ? 0x765 : 0x102) >> (seg * 4)) & 7; if (seg == 0) { c1 = 11; mode = 2; } }
      const int rblk = qb * 8 + rbl;
      uint32_t q[4], qa[4];
      {
        const uint32_t* qp = (const uint32_t*)(gQ + (size_t)head * 65536 + (size_t)(rblk * 64 + w * 16 + g) * 32) + t;
        q[0] = __ldcg(qp); q[1] = __ldcg(qp + 64); q[2] = __ldcg(qp + 4); q[3] = __ldcg(qp + 68);
      }
      const uint32_t va = sb + SM_A + 4096 + c0 * 8192;
      const uint64_t dV0 = mkdesc(va, sb + SM_ONES - va, 256, 3);
      const uint32_t cend = (uint32_t)(dV0 + (uint64_t)(c1 - c0) * 16 * VS);
      float o[12], bias[2];
      {
        const int nmax = exact ? (c1 - c0) * 2 : 1;
        float s[32];
        uint32_t p0[16], p1[16];
        float mp0 = -INFINITY, mp1 = -INFINITY, mm0 = -INFINITY, mm1 = -INFINITY;
#pragma unroll 1
        for (int i = 0; i < nmax; i++) {
          wg_fence();
          wg_rs_n64<0, 0>(s, q, dV0 - 256 + (i >> 1) * 512 + (i & 1) * 128);
          wg_commit();
          wg_wait<0>();
          pin<32>(s);
#pragma unroll
          for (int j = 0; j < 8; j++) {
            if ((POLYMASK >> j) & 1) { mp0 = fmaxf(mp0, fmaxf(s[4 * j], s[4 * j + 1])); mp1 = fmaxf(mp1, fmaxf(s[4 * j + 2], s[4 * j + 3])); }
            else { mm0 = fmaxf(mm0, fmaxf(s[4 * j], s[4 * j + 1])); mm1 = fmaxf(mm1, fmaxf(s[4 * j + 2], s[4 * j + 3])); }
          }
        }
#pragma unroll
        for (int r = 0; r < 2; r++) {
          float v = fmaxf(r ? mm1 : mm0, ((r ? mp1 : mp0) * 0x1p71f) * 0x1p71f);
          v = fmaxf(v, __shfl_xor_sync(~0u, v, 1));
          v = fmaxf(v, __shfl_xor_sync(~0u, v, 2));
          bias[r] = rintf(64.f - v);
          const float y = bias[r] * 0x1p-71f, hi = bfr(y), mid = bfr(y - hi);
          qa[r] = t == 0 ? packbf(hi, mid) : t == 1 ? packbf(y - hi - mid, 0x1p-71f) : t == 2 ? 0x00001C00u : 0u;
          qa[2 + r] = qa[r] & zero;
        }
        clear<12>(o);
        uint64_t c = dV0;
        wg_fence();
        wg_rs_n64<0, 0>(s, qa, dBias);
        wg_rs_n64<0, 1>(s, q, c - 256);
        wg_commit();
        wg_wait<0>();
#pragma unroll 1
        do {
          softmax64(s, p0, half2);
          wg_fence();
          wg_rs_n64<0, 0>(s, qa, dBias);
          wg_rs_n64<0, 1>(s, q, c - 128);
          wg_commit();
#pragma unroll
          for (int k = 0; k < 4; k++) wg_rs_n24<1, 1>(o, p0 + 4 * k, c + k * VS);
          wg_commit();
          wg_wait<1>();
          softmax64(s, p1, half2);
          wg_fence();
          wg_rs_n64<0, 0>(s, qa, dBias);
          wg_rs_n64<0, 1>(s, q, c + 256);
          wg_commit();
#pragma unroll
          for (int k = 0; k < 4; k++) wg_rs_n24<1, 1>(o, p1 + 4 * k, c + (4 + k) * VS);
          wg_commit();
          c += 16 * VS;
          wg_wait<1>();
        } while ((uint32_t)c != cend);
        wg_wait<0>();
        pin<12>(o);
      }
      exact = __all_sync(~0u, bar_or(10 + wg, 128, !exact && !(o[8] < 0x1p90f && o[10] < 0x1p90f)));
      if (exact) { seg--; continue; }
      if (mode == 1) {
        float* mp = (float*)(smem + SM_MERGE + seg * 6144) + (tid & 127);
        o[9] = bias[0]; o[11] = bias[1];
#pragma unroll
        for (int i = 0; i < 12; i++) mp[i * 128] = o[i];
        bar_arrive(8 + seg, 256);
        continue;
      }
      if (mode == 2) {
        const float* mp = (const float*)(smem + SM_MERGE + (wg >> 1) * 6144) + (tid & 127);
        bar_sync(8 + (wg >> 1), 256);
#pragma unroll
        for (int r = 0; r < 2; r++) {
          const float bo = mp[(9 + 2 * r) * 128], bm = fminf(bo, bias[r]);
          const float fa = ex2(0.5f * (bm - bias[r])), fb = ex2(0.5f * (bm - bo));
          o[2 * r] = o[2 * r] * fa * fa + mp[(2 * r) * 128] * fb * fb;
          o[2 * r + 1] = o[2 * r + 1] * fa * fa + mp[(2 * r + 1) * 128] * fb * fb;
          o[4 + 2 * r] = o[4 + 2 * r] * fa * fa + mp[(4 + 2 * r) * 128] * fb * fb;
          o[5 + 2 * r] = o[5 + 2 * r] * fa * fa + mp[(5 + 2 * r) * 128] * fb * fb;
          o[8 + 2 * r] = o[8 + 2 * r] * fa * fa + mp[(8 + 2 * r) * 128] * fb * fb;
        }
      }
      if (seg == nseg - 1 && lane == 0) mbar_arrive(sb + B_ADONE);
#pragma unroll
      for (int r = 0; r < 2; r++) {
        const float inv = rcp(o[8 + 2 * r]);
        const uint32_t a = packbf(o[2 * r] * inv, o[2 * r + 1] * inv), c = packbf(o[4 + 2 * r] * inv, o[5 + 2 * r] * inv);
        const uint32_t e = __shfl_xor_sync(~0u, (t & 2) ? a : c, 2);
        *(uint2*)(gO + (size_t)(rblk * 8 + (head >> 2)) * 8192 + ((head & 3) * 2 + (t & 1)) * 1024 + (2 * w + r) * 128 + g * 16 + (t & 2) * 4) =
            (t & 2) ? make_uint2(e, c) : make_uint2(a, e);
      }
      bar_arrive(13 + wg, 160);
      TSTAMP(wg, 9 + seg);
    }
  } else {
    uint32_t gate[32];
    const uint64_t dB0 = mkdesc(sb + SM_RING, 8192, 1024, 1);
    {
      const uint64_t dA0 = mkdesc(sb + SM_RING + 8192, 1024, 128, 0);
      float acc[64];
      clear<64>(acc);
      int slot = 0;
      uint32_t ph = 0;
#pragma unroll 1
      for (int n = 0; n < 28; n++) {
        mbar_wait_sleep(sb + B_FULL2 + 8 * slot, ph, 100);
        const uint64_t dA = dA0 + slot * 1536, dB = dB0 + slot * 1536;
        wg_fence();
#pragma unroll
        for (int k = 0; k < 4; k++) {
          wg_ss_n64<1>(acc, dA + k * 128, dB + k * 128);
          wg_ss_n64<1>(acc + 32, dA + 512 + k * 128, dB + k * 128);
        }
        wg_commit();
        wg_wait<0>();
        if (lane == 0) mbar_arrive(sb + B_EMPTY2 + 8 * slot);
        if (++slot == 3) { slot = 0; ph ^= 1; }
      }
      pin<64>(acc);
#pragma unroll
      for (int i = 0; i < 32; i++) {
        const float f0 = bfr(acc[2 * i]), f1 = bfr(acc[2 * i + 1]);
        gate[i] = packbf(f0 * rcp(1.f + ex2(-LOG2E * f0)), f1 * rcp(1.f + ex2(-LOG2E * f1)));
      }
    }
    TSTAMP(wg, 8);
#pragma unroll
    for (int pass = 0; pass < 2; pass++) {
      const size_t off = (size_t)((pass ? rLate : rEarly) * 64 + w * 16 + g) * DM + cg * 64 + (t & 1) * 8 + (t & 2) * 2;
      uint2 xr[8];
#pragma unroll
      for (int i = 0; i < 8; i++) xr[i] = __ldg((const uint2*)(x + off + (i & 1) * 8 * DM + (i >> 1) * 16));
      float acc[32];
      clear<32>(acc);
      if (pass == 0) {
        const uint64_t dA0 = mkdesc(sb + SM_RING + 65536, 1024, 128, 0);
        mbar_wait_sleep(sb + B_WO, 0, 200);
#pragma unroll 1
        for (int n = 0; n < 8; n++) {
          mbar_wait_sleep(sb + B_OE + 8 * (n & 1), (n >> 1) & 1, 200);
          wg_fence();
#pragma unroll
          for (int k = 0; k < 4; k++) wg_ss_n64<1>(acc, dA0 + (n & 1) * 512 + k * 128, dB0 + n * 512 + k * 128);
          wg_commit();
          wg_wait<0>();
          if (lane == 0) mbar_arrive(sb + B_OEE + 8 * (n & 1));
        }
      } else {
        mbar_wait_sleep(sb + B_ADONE, 0, 200);
        const uint64_t dA = mkdesc(sb + SM_A, 1024, 128, 0);
#pragma unroll 1
        for (int n = 0; n < 4; n++) {
          mbar_wait(sb + B_O + 8 * n, 0);
          wg_fence();
#pragma unroll
          for (int k = 0; k < 8; k++) wg_ss_n64<1>(acc, dA + (n * 8 + k) * 128, dB0 + (n * 8 + k) * 128);
          wg_commit();
        }
        wg_wait<0>();
      }
      pin<32>(acc);
      TSTAMP(wg, 9 + 2 * pass);
#pragma unroll
      for (int i = 0; i < 8; i++) {
        const int ia = (i >> 1) * 4 + (i & 1), ib = ia + 2;
        const uint32_t ya = hmul(packbf(acc[2 * ia], acc[2 * ia + 1]), gate[pass * 16 + ia]);
        const uint32_t yb = hmul(packbf(acc[2 * ib], acc[2 * ib + 1]), gate[pass * 16 + ib]);
        const uint32_t e = __shfl_xor_sync(~0u, (t & 1) ? ya : yb, 1);
        const uint32_t lo = (t & 1) ? e : ya, hi = (t & 1) ? yb : e;
        *(uint2*)(out + off + (i & 1) * 8 * DM + (i >> 1) * 16) = make_uint2(hadd(xr[i].x, lo), hadd(xr[i].y, hi));
      }
      TSTAMP(wg, 10 + 2 * pass);
    }
  }
}

typedef CUresult (*EncodeFn)(CUtensorMap*, CUtensorMapDataType, cuuint32_t, void*, const cuuint64_t*, const cuuint64_t*, const cuuint32_t*,
                             const cuuint32_t*, CUtensorMapInterleave, CUtensorMapSwizzle, CUtensorMapL2promotion, CUtensorMapFloatOOBfill);

void make_map(EncodeFn enc, CUtensorMap* m, void* p, int rows, int cols) {
  const cuuint64_t dims[2] = {(cuuint64_t)cols, (cuuint64_t)rows}, strides[1] = {(cuuint64_t)cols * 2};
  const cuuint32_t box[2] = {64, 64}, es[2] = {1, 1};
  enc(m, CU_TENSOR_MAP_DATA_TYPE_BFLOAT16, 2, p, dims, strides, box, es, CU_TENSOR_MAP_INTERLEAVE_NONE, CU_TENSOR_MAP_SWIZZLE_128B,
      CU_TENSOR_MAP_L2_PROMOTION_L2_128B, CU_TENSOR_MAP_FLOAT_OOB_FILL_NONE);
}

}

extern "C" void kernel_launch(void* const* d_in, const int* in_sizes, int n_in, void* d_out, int out_size) {
  (void)in_sizes; (void)n_in; (void)out_size;
  void* fn = nullptr;
  cudaDriverEntryPointQueryResult qr;
  cudaGetDriverEntryPoint("cuTensorMapEncodeTiled", &fn, cudaEnableDefault, &qr);
  EncodeFn enc = (EncodeFn)fn;
  CUtensorMap mQKV, mW1, mW3, mW2, mWO;
  make_map(enc, &mQKV, d_in[1], DM, 3 * DM);
  make_map(enc, &mWO, d_in[2], DM, DM);
  make_map(enc, &mW1, d_in[4], DM, FF);
  make_map(enc, &mW3, d_in[5], DM, FF);
  make_map(enc, &mW2, d_in[6], FF, DM);
  cudaFuncSetAttribute(fused_kernel, cudaFuncAttributeMaxDynamicSharedMemorySize, SM_TOTAL);
  fused_kernel<<<128, NTHREADS, SM_TOTAL>>>(mQKV, mW1, mW3, mW2, mWO, (const bf16*)d_in[0], (bf16*)d_out, 0u);
}
```

```cpp
#include <cuda_runtime.h>
#include <cuda_bf16.h>
#include <cuda.h>
#include <stdint.h>

namespace {

typedef __nv_bfloat16 bf16;
constexpr int SEQ = 2048, DM = 512, FF = 1792;
constexpr int NTHREADS = 640;
constexpr int NSLOT = 5;
constexpr uint32_t POLYMASK = 0x57;

constexpr uint32_t SM_A     = 0;
constexpr uint32_t SM_RING  = 131072;
constexpr uint32_t SM_ONES  = SM_RING + 81920;
constexpr uint32_t SM_BIAS  = SM_ONES + 512;
constexpr uint32_t SM_MERGE = SM_BIAS + 2048;
constexpr uint32_t SM_RSTD  = SM_MERGE + 12288;
constexpr uint32_t SM_DELTA = SM_RSTD + 512;
constexpr uint32_t SM_BAR   = SM_DELTA + 512;
constexpr uint32_t B_FULL1  = SM_BAR;
constexpr uint32_t B_EMPTY1 = B_FULL1 + 8 * 2 * NSLOT;
constexpr uint32_t B_KV     = B_EMPTY1 + 8 * NSLOT;
constexpr uint32_t B_FULL2  = B_KV + 64;
constexpr uint32_t B_OE     = B_FULL2 + 24;
constexpr uint32_t B_WO     = B_OE + 16;
constexpr uint32_t B_O      = B_WO + 8;
constexpr uint32_t B_EMPTY2 = B_O + 32;
constexpr uint32_t B_OEE    = B_EMPTY2 + 24;
constexpr uint32_t B_ADONE  = B_OEE + 16;
constexpr uint32_t SM_TOTAL = B_ADONE + 8;

__device__ __align__(1024) uint8_t gQ[32 * SEQ * 32];
__device__ __align__(1024) uint8_t gKV[32 * 16 * 8192];
__device__ __align__(1024) uint8_t gH[32 * 28 * 8192];
__device__ __align__(1024) uint8_t gO[32 * 8 * 8192];
__device__ uint32_t gFlag[72 * 32];
constexpr int F_QKV = 0, F_H = 8, F_O = 40;
#define TSTAMP(role, i)

template<int TB, int SD> __device__ __forceinline__ void wg_rs_n24(float* d, const uint32_t* a, uint64_t db) {
  if (SD)
    asm volatile("wgmma.mma_async.sync.aligned.m64n24k16.f32.bf16.bf16 {%0,%1,%2,%3,%4,%5,%6,%7,%8,%9,%10,%11}, {%12,%13,%14,%15}, %16, 1, 1, 1, %17;"
      : "+f"(d[0]),"+f"(d[1]),"+f"(d[2]),"+f"(d[3]),"+f"(d[4]),"+f"(d[5]),"+f"(d[6]),"+f"(d[7]),"+f"(d[8]),"+f"(d[9]),"+f"(d[10]),"+f"(d[11])
      : "r"(a[0]), "r"(a[1]), "r"(a[2]), "r"(a[3]), "l"(db), "n"(TB));
  else
    asm volatile("wgmma.mma_async.sync.aligned.m64n24k16.f32.bf16.bf16 {%0,%1,%2,%3,%4,%5,%6,%7,%8,%9,%10,%11}, {%12,%13,%14,%15}, %16, 0, 1, 1, %17;"
      : "=f"(d[0]),"=f"(d[1]),"=f"(d[2]),"=f"(d[3]),"=f"(d[4]),"=f"(d[5]),"=f"(d[6]),"=f"(d[7]),"=f"(d[8]),"=f"(d[9]),"=f"(d[10]),"=f"(d[11])
      : "r"(a[0]), "r"(a[1]), "r"(a[2]), "r"(a[3]), "l"(db), "n"(TB));
}
template<int TB, int SD> __device__ __forceinline__ void wg_rs_n64(float* d, const uint32_t* a, uint64_t db) {
  if (SD)
    asm volatile("wgmma.mma_async.sync.aligned.m64n64k16.f32.bf16.bf16 {%0,%1,%2,%3,%4,%5,%6,%7,%8,%9,%10,%11,%12,%13,%14,%15,%16,%17,%18,%19,%20,%21,%22,%23,%24,%25,%26,%27,%28,%29,%30,%31}, {%32,%33,%34,%35}, %36, 1, 1, 1, %37;"
      : "+f"(d[0]),"+f"(d[1]),"+f"(d[2]),"+f"(d[3]),"+f"(d[4]),"+f"(d[5]),"+f"(d[6]),"+f"(d[7]),"+f"(d[8]),"+f"(d[9]),"+f"(d[10]),"+f"(d[11]),"+f"(d[12]),"+f"(d[13]),"+f"(d[14]),"+f"(d[15]),"+f"(d[16]),"+f"(d[17]),"+f"(d[18]),"+f"(d[19]),"+f"(d[20]),"+f"(d[21]),"+f"(d[22]),"+f"(d[23]),"+f"(d[24]),"+f"(d[25]),"+f"(d[26]),"+f"(d[27]),"+f"(d[28]),"+f"(d[29]),"+f"(d[30]),"+f"(d[31])
      : "r"(a[0]), "r"(a[1]), "r"(a[2]), "r"(a[3]), "l"(db), "n"(TB));
  else
    asm volatile("wgmma.mma_async.sync.aligned.m64n64k16.f32.bf16.bf16 {%0,%1,%2,%3,%4,%5,%6,%7,%8,%9,%10,%11,%12,%13,%14,%15,%16,%17,%18,%19,%20,%21,%22,%23,%24,%25,%26,%27,%28,%29,%30,%31}, {%32,%33,%34,%35}, %36, 0, 1, 1, %37;"
      : "=f"(d[0]),"=f"(d[1]),"=f"(d[2]),"=f"(d[3]),"=f"(d[4]),"=f"(d[5]),"=f"(d[6]),"=f"(d[7]),"=f"(d[8]),"=f"(d[9]),"=f"(d[10]),"=f"(d[11]),"=f"(d[12]),"=f"(d[13]),"=f"(d[14]),"=f"(d[15]),"=f"(d[16]),"=f"(d[17]),"=f"(d[18]),"=f"(d[19]),"=f"(d[20]),"=f"(d[21]),"=f"(d[22]),"=f"(d[23]),"=f"(d[24]),"=f"(d[25]),"=f"(d[26]),"=f"(d[27]),"=f"(d[28]),"=f"(d[29]),"=f"(d[30]),"=f"(d[31])
      : "r"(a[0]), "r"(a[1]), "r"(a[2]), "r"(a[3]), "l"(db), "n"(TB));
}
template<int TB> __device__ __forceinline__ void wg_ss_n64(float* d, uint64_t da, uint64_t db) {
  asm volatile("wgmma.mma_async.sync.aligned.m64n64k16.f32.bf16.bf16 {%0,%1,%2,%3,%4,%5,%6,%7,%8,%9,%10,%11,%12,%13,%14,%15,%16,%17,%18,%19,%20,%21,%22,%23,%24,%25,%26,%27,%28,%29,%30,%31}, %32, %33, 1, 1, 1, 0, %34;"
    : "+f"(d[0]),"+f"(d[1]),"+f"(d[2]),"+f"(d[3]),"+f"(d[4]),"+f"(d[5]),"+f"(d[6]),"+f"(d[7]),"+f"(d[8]),"+f"(d[9]),"+f"(d[10]),"+f"(d[11]),"+f"(d[12]),"+f"(d[13]),"+f"(d[14]),"+f"(d[15]),"+f"(d[16]),"+f"(d[17]),"+f"(d[18]),"+f"(d[19]),"+f"(d[20]),"+f"(d[21]),"+f"(d[22]),"+f"(d[23]),"+f"(d[24]),"+f"(d[25]),"+f"(d[26]),"+f"(d[27]),"+f"(d[28]),"+f"(d[29]),"+f"(d[30]),"+f"(d[31])
    : "l"(da), "l"(db), "n"(TB));
}
template<int TB> __device__ __forceinline__ void wg_ss_n128(float* d, uint64_t da, uint64_t db) {
  asm volatile("wgmma.mma_async.sync.aligned.m64n128k16.f32.bf16.bf16 {%0,%1,%2,%3,%4,%5,%6,%7,%8,%9,%10,%11,%12,%13,%14,%15,%16,%17,%18,%19,%20,%21,%22,%23,%24,%25,%26,%27,%28,%29,%30,%31,%32,%33,%34,%35,%36,%37,%38,%39,%40,%41,%42,%43,%44,%45,%46,%47,%48,%49,%50,%51,%52,%53,%54,%55,%56,%57,%58,%59,%60,%61,%62,%63}, %64, %65, 1, 1, 1, 0, %66;"
    : "+f"(d[0]),"+f"(d[1]),"+f"(d[2]),"+f"(d[3]),"+f"(d[4]),"+f"(d[5]),"+f"(d[6]),"+f"(d[7]),"+f"(d[8]),"+f"(d[9]),"+f"(d[10]),"+f"(d[11]),"+f"(d[12]),"+f"(d[13]),"+f"(d[14]),"+f"(d[15]),"+f"(d[16]),"+f"(d[17]),"+f"(d[18]),"+f"(d[19]),"+f"(d[20]),"+f"(d[21]),"+f"(d[22]),"+f"(d[23]),"+f"(d[24]),"+f"(d[25]),"+f"(d[26]),"+f"(d[27]),"+f"(d[28]),"+f"(d[29]),"+f"(d[30]),"+f"(d[31]),"+f"(d[32]),"+f"(d[33]),"+f"(d[34]),"+f"(d[35]),"+f"(d[36]),"+f"(d[37]),"+f"(d[38]),"+f"(d[39]),"+f"(d[40]),"+f"(d[41]),"+f"(d[42]),"+f"(d[43]),"+f"(d[44]),"+f"(d[45]),"+f"(d[46]),"+f"(d[47]),"+f"(d[48]),"+f"(d[49]),"+f"(d[50]),"+f"(d[51]),"+f"(d[52]),"+f"(d[53]),"+f"(d[54]),"+f"(d[55]),"+f"(d[56]),"+f"(d[57]),"+f"(d[58]),"+f"(d[59]),"+f"(d[60]),"+f"(d[61]),"+f"(d[62]),"+f"(d[63])
    : "l"(da), "l"(db), "n"(TB));
}

__device__ __forceinline__ void wg_fence() { asm volatile("wgmma.fence.sync.aligned;" ::: "memory"); }
__device__ __forceinline__ void wg_commit() { asm volatile("wgmma.commit_group.sync.aligned;" ::: "memory"); }
template <int N> __device__ __forceinline__ void wg_wait() { asm volatile("wgmma.wait_group.sync.aligned %0;" ::"n"(N) : "memory"); }
template <int N> __device__ __forceinline__ void pin(float* r) {
#pragma unroll
  for (int i = 0; i < N; i++) asm volatile("" : "+f"(r[i])::"memory");
}
template <int N> __device__ __forceinline__ void clear(float* r) {
#pragma unroll
  for (int i = 0; i < N; i++) r[i] = 0.f;
  pin<N>(r);
}
template <int N> __device__ __forceinline__ void pin(uint32_t* r) {
#pragma unroll
  for (int i = 0; i < N; i++) asm volatile("" : "+r"(r[i])::"memory");
}
__device__ __forceinline__ uint64_t mkdesc(uint32_t addr, uint32_t lbo, uint32_t sbo, uint32_t swz) {
  return (uint64_t)((addr & 0x3FFFF) >> 4) | ((uint64_t)(lbo >> 4) << 16) | ((uint64_t)(sbo >> 4) << 32) | ((uint64_t)swz << 62);
}
__device__ __forceinline__ void mbar_init(uint32_t b, int c) { asm volatile("mbarrier.init.shared::cta.b64 [%0], %1;" ::"r"(b), "r"(c) : "memory"); }
__device__ __forceinline__ void mbar_expect(uint32_t b, int n) { asm volatile("mbarrier.arrive.expect_tx.shared::cta.b64 _, [%0], %1;" ::"r"(b), "r"(n) : "memory"); }
__device__ __forceinline__ void mbar_arrive(uint32_t b) { asm volatile("mbarrier.arrive.shared::cta.b64 _, [%0];" ::"r"(b) : "memory"); }
__device__ __forceinline__ bool mbar_try(uint32_t b, uint32_t ph) {
  uint32_t ok;
  asm volatile("{.reg .pred p; mbarrier.try_wait.parity.shared::cta.b64 p, [%1], %2; selp.u32 %0, 1, 0, p;}" : "=r"(ok) : "r"(b), "r"(ph) : "memory");
  return ok;
}
__device__ __forceinline__ void mbar_wait(uint32_t b, uint32_t ph) {
  if (mbar_try(b, ph)) return;
#pragma unroll 1
  for (int i = 0; i < (1 << 16); i++) {
    uint32_t ok;
    asm volatile("{.reg .pred p; mbarrier.try_wait.parity.shared::cta.b64 p, [%1], %2, 20000; selp.u32 %0, 1, 0, p;}" : "=r"(ok) : "r"(b), "r"(ph) : "memory");
    if (ok) return;
  }
  __trap();
}
__device__ __forceinline__ void bulk_load(uint32_t dst, const void* src, int bytes, uint32_t bar) {
  asm volatile("cp.async.bulk.shared::cluster.global.mbarrier::complete_tx::bytes [%0], [%1], %2, [%3];" ::"r"(dst), "l"(src), "r"(bytes), "r"(bar) : "memory");
}
__device__ __forceinline__ void tma_load(uint32_t dst, const CUtensorMap* m, int c0, int c1, uint32_t bar) {
  asm volatile("cp.async.bulk.tensor.2d.shared::cluster.global.mbarrier::complete_tx::bytes [%0], [%1, {%2, %3}], [%4];" ::"r"(dst), "l"(m), "r"(c0), "r"(c1), "r"(bar) : "memory");
}
__device__ __forceinline__ void tma_prefetch(const CUtensorMap* m, int c0, int c1) {
  asm volatile("cp.async.bulk.prefetch.tensor.2d.L2.global [%0, {%1, %2}];" ::"l"(m), "r"(c0), "r"(c1) : "memory");
}
__device__ __forceinline__ bool elect() {
  uint32_t r;
  asm volatile("{.reg .pred p; elect.sync _|p, 0xffffffff; selp.u32 %0, 1, 0, p;}" : "=r"(r));
  return r;
}
__device__ __forceinline__ void bar_sync(int id, int n) { asm volatile("bar.sync %0, %1;" ::"r"(id), "r"(n) : "memory"); }
__device__ __forceinline__ void bar_arrive(int id, int n) { asm volatile("bar.arrive %0, %1;" ::"r"(id), "r"(n) : "memory"); }
__device__ __forceinline__ bool bar_or(int id, int n, bool v) {
  uint32_t r;
  asm volatile("{.reg .pred p, q; setp.ne.u32 q, %3, 0; bar.red.or.pred p, %1, %2, q; selp.u32 %0, 1, 0, p;}" : "=r"(r) : "r"(id), "r"(n), "r"((uint32_t)v) : "memory");
  return r;
}
__device__ __forceinline__ void flag_add(int f) { asm volatile("red.release.gpu.global.add.u32 [%0], 1;" ::"l"(gFlag + f * 32) : "memory"); }
__device__ __forceinline__ void flag_wait(int f, uint32_t target, uint32_t ns) {
#pragma unroll 1
  for (int i = 0; i < (1 << 22); i++) {
    uint32_t v;
    asm volatile("ld.acquire.gpu.global.u32 %0, [%1];" : "=r"(v) : "l"(gFlag + f * 32) : "memory");
    if ((int)(v - target) >= 0) { asm volatile("fence.proxy.async.global;" ::: "memory"); return; }
    __nanosleep(ns);
  }
  __trap();
}
__device__ __forceinline__ float ex2(float x) { float y; asm("ex2.approx.ftz.f32 %0, %1;" : "=f"(y) : "f"(x)); return y; }
__device__ __forceinline__ float rcp(float x) { float y; asm("rcp.approx.ftz.f32 %0, %1;" : "=f"(y) : "f"(x)); return y; }
__device__ __forceinline__ uint32_t packbf(float lo, float hi) { uint32_t d; asm("cvt.rn.bf16x2.f32 %0, %1, %2;" : "=r"(d) : "f"(hi), "f"(lo)); return d; }
__device__ __forceinline__ float bfr(float x) { return __bfloat162float(__float2bfloat16(x)); }
__device__ __forceinline__ float bf_lo(uint32_t u) { return __uint_as_float(u << 16); }
__device__ __forceinline__ float bf_hi(uint32_t u) { return __uint_as_float(u & 0xFFFF0000u); }
__device__ __forceinline__ uint32_t hmul(uint32_t a, uint32_t b) { uint32_t d; asm("mul.rn.bf16x2 %0, %1, %2;" : "=r"(d) : "r"(a), "r"(b)); return d; }
__device__ __forceinline__ uint32_t hadd(uint32_t a, uint32_t b) { uint32_t d; asm("add.rn.bf16x2 %0, %1, %2;" : "=r"(d) : "r"(a), "r"(b)); return d; }
__device__ __forceinline__ uint32_t hsub(uint32_t a, uint32_t b) { uint32_t d; asm("sub.rn.bf16x2 %0, %1, %2;" : "=r"(d) : "r"(a), "r"(b)); return d; }
constexpr float LOG2E = 1.4426950408889634f;

__device__ __forceinline__ uint32_t exp_poly(float lo, float hi, uint32_t half2) {
  uint32_t u, mh, p;
  asm("cvt.pack.sat.s16.s32 %0, %1, %2;" : "=r"(u) : "r"(__float_as_uint(hi)), "r"(__float_as_uint(lo)));
  asm("lop3.b32 %0, %1, 0x007F007F, %2, 0xEA;" : "=r"(mh) : "r"(u), "r"(half2));
  asm("fma.rn.bf16x2 %0, %1, %2, %3;" : "=r"(p) : "r"(u), "r"(mh), "r"(u & 0xFF80FF80u));
  return p;
}
__device__ __forceinline__ void softmax64(float* s, uint32_t* p, uint32_t half2) {
  pin<32>(s);
#pragma unroll
  for (int j = 0; j < 8; j++) {
#pragma unroll
    for (int r = 0; r < 2; r++) {
      const float a = s[4 * j + 2 * r], b = s[4 * j + 2 * r + 1];
      p[2 * j + r] = ((POLYMASK >> j) & 1) ? exp_poly(a, b, half2) : packbf(ex2(a), ex2(b));
    }
  }
  pin<16>(p);
}

struct Tile { int kind, c0, c1; };
__device__ __forceinline__ Tile tile_of(int cg, int t) {
  const int c2 = cg >> 1;
  Tile r;
  if (cg & 1) {
    if (t == 0) { r.kind = 1; r.c0 = c2 * 128; r.c1 = r.c0 + 64; }
    else { r.kind = 2; r.c0 = r.c1 = (7 * c2 + 2 + t) * 64; }
  } else {
    if (t < 2) { r.kind = 0; r.c0 = 512 + c2 * 128 + t * 64; r.c1 = r.c0 + 512; }
    else { r.kind = 2; r.c0 = r.c1 = (7 * c2 + t - 2) * 64; }
  }
  return r;
}

__global__ void __launch_bounds__(NTHREADS, 1)
fused_kernel(const __grid_constant__ CUtensorMap mQKV, const __grid_constant__ CUtensorMap mW1, const __grid_constant__ CUtensorMap mW3,
             const __grid_constant__ CUtensorMap mW2, const __grid_constant__ CUtensorMap mWO, const bf16* __restrict__ x, bf16* __restrict__ out,
             uint32_t zero) {
  extern __shared__ __align__(1024) uint8_t smem[];
  const uint32_t sb = (uint32_t)__cvta_generic_to_shared(smem);
  const int tid = threadIdx.x, lane = tid & 31, g = lane >> 2, t = lane & 3;
  const int warp = __shfl_sync(~0u, tid >> 5, 0), wg = warp >> 2, w = warp & 3;
  const int b = blockIdx.x;
  const int rb = b >> 3, cg = b & 7;
  const int head = b & 31, qb = b >> 5;
  const int rEarly = (rb >> 2) * 8 + ((0x3052 >> ((rb & 3) * 4)) & 7), rLate = (rb >> 2) * 8 + ((0x6741 >> ((rb & 3) * 4)) & 7);

  if (wg == 4) {
    asm volatile("setmaxnreg.dec.sync.aligned.u32 32;");
    if (w == 0) {
      uint32_t epoch;
      asm volatile("ld.relaxed.gpu.global.u32 %0, [%1];" : "=r"(epoch) : "l"(gFlag + F_O * 32) : "memory");
      if (lane < 2 * NSLOT) mbar_init(sb + B_FULL1 + 8 * lane, 1);
      if (lane < NSLOT) mbar_init(sb + B_EMPTY1 + 8 * lane, 8);
      if (lane < 24) mbar_init(sb + B_KV + 8 * lane, lane < 18 ? 1 : lane < 23 ? 4 : 12);
      asm volatile("fence.mbarrier_init.release.cluster;" ::: "memory");
      asm volatile("fence.proxy.async.shared::cta;" ::: "memory");
      __syncwarp();
      bar_arrive(1, 544);
      int slot = 0;
      uint32_t ph = 1;
#pragma unroll 1
      for (int tI = 0; tI < 5; tI++) {
        const Tile tl = tile_of(cg, tI);
        const CUtensorMap *m0 = tl.kind == 2 ? &mW1 : &mQKV, *m1 = tl.kind == 2 ? &mW3 : &mQKV;
#pragma unroll 1
        for (int k = 0; k < 8; k++) {
          const uint32_t full = sb + B_FULL1 + 8 * ((tI & 1) * NSLOT + slot), dst = sb + SM_RING + slot * 16384;
          if (tI == 0 && k == NSLOT) {
            const int i = 2 * NSLOT + rb + lane * 16;
            if (i < 80) {
              const Tile tp = tile_of(cg, i >> 4);
              tma_prefetch((i & 1) ? (tp.kind == 2 ? &mW3 : &mQKV) : (tp.kind == 2 ? &mW1 : &mQKV), (i & 1) ? tp.c1 : tp.c0, ((i >> 1) & 7) * 64);
            }
            __syncwarp();
          }
          mbar_wait(sb + B_EMPTY1 + 8 * slot, ph);
          if (elect()) {
            mbar_expect(full, 16384);
            tma_load(dst, m0, tl.c0, k * 64, full);
            tma_load(dst + 8192, m1, tl.c1, k * 64, full);
          }
          if (++slot == NSLOT) { slot = 0; ph ^= 1; }
        }
      }
      epoch = (epoch >> 5) + 1;
      flag_wait(F_QKV + (head >> 2), epoch * 32, 32);
#pragma unroll 1
      for (int j = 0; j < 8; j++) {
        if (j >= 8 - NSLOT) {
          mbar_wait(sb + B_EMPTY1 + 8 * slot, ph);
          if (++slot == NSLOT) { slot = 0; ph ^= 1; }
        }
        if (elect()) {
          mbar_expect(sb + B_KV + 8 * j, 16384);
          bulk_load(sb + SM_A + j * 16384, gKV + (size_t)head * 131072 + j * 16384, 16384, sb + B_KV + 8 * j);
        }
      }
      flag_wait(F_H + rEarly, epoch * 28, 100);
      flag_wait(F_H + rLate, epoch * 28, 100);
      slot = 0; ph = 1;
#pragma unroll 1
      for (int n = 0; n < 31; n++) {
        const uint32_t full = sb + B_FULL2 + 8 * slot, dst = sb + SM_RING + slot * 24576;
        mbar_wait(sb + B_EMPTY2 + 8 * slot, ph);
        if (n < 28 && elect()) {
          mbar_expect(full, 24576);
          tma_load(dst, &mW2, cg * 64, n * 64, full);
          bulk_load(dst + 8192, gH + (size_t)(rEarly * 28 + n) * 8192, 8192, full);
          bulk_load(dst + 16384, gH + (size_t)(rLate * 28 + n) * 8192, 8192, full);
        }
        if (++slot == 3) { slot = 0; ph ^= 1; }
      }
      if (elect()) {
        mbar_expect(sb + B_WO, 65536);
#pragma unroll 1
        for (int k = 0; k < 8; k++) tma_load(sb + SM_RING + k * 8192, &mWO, cg * 64, k * 64, sb + B_WO);
      }
      flag_wait(F_O + rEarly, epoch * 32, 200);
#pragma unroll 1
      for (int n = 0; n < 8; n++) {
        mbar_wait(sb + B_OEE + 8 * (n & 1), ((n >> 1) & 1) ^ 1);
        if (elect()) {
          mbar_expect(sb + B_OE + 8 * (n & 1), 8192);
          bulk_load(sb + SM_RING + 65536 + (n & 1) * 8192, gO + (size_t)(rEarly * 8 + n) * 8192, 8192, sb + B_OE + 8 * (n & 1));
        }
      }
      mbar_wait(sb + B_ADONE, 0);
      flag_wait(F_O + rLate, epoch * 32, 20);
      if (elect()) {
#pragma unroll
        for (int i = 0; i < 4; i++) {
          mbar_expect(sb + B_O + 8 * i, 16384);
          bulk_load(sb + SM_A + i * 16384, gO + (size_t)rLate * 65536 + i * 16384, 16384, sb + B_O + 8 * i);
        }
      }
    } else {
      if (w < 3) {
#pragma unroll 1
        for (int tI = w - 1; tI < 5; tI += 2) {
          const Tile tl = tile_of(cg, tI);
          bar_sync(3 + w, 288);
          if (lane < (tl.kind ? 2 : 1)) flag_add(tl.kind == 2 ? F_H + rb * 2 + lane : F_QKV + ((tl.c0 >> 6) & 7) + lane);
          __syncwarp();
        }
      }
#pragma unroll 1
      for (int i = 0; i < (w == 2 ? 2 : 3); i++) {
        bar_sync(12 + w, 160);
        if (lane == 0) flag_add(F_O + qb * 8 + (((w == 1 ? 0x102 : w == 2 ? 0x43 : 0x765) >> (i * 4)) & 7));
        __syncwarp();
      }
    }
    return;
  }

  TSTAMP(wg, 0);
  uint4 xv[16];
  {
    const uint4* xp = (const uint4*)(x + (size_t)(rb * 128 + warp * 8 + g) * DM);
#pragma unroll
    for (int j = 0; j < 16; j++) xv[j] = __ldg(xp + 4 * (j ^ (g & 1)) + t);
  }
  asm volatile("setmaxnreg.inc.sync.aligned.u32 112;");

  {
    if (tid < 128) ((uint32_t*)(smem + SM_ONES))[tid] = 0x3F803F80u;
    {
      const int n = tid >> 3, k = (tid & 7) * 2;
      const bool poly = (POLYMASK >> (n >> 3)) & 1;
      const float cm = -127.f + 0.5849625f - 0.0020f, chi = bfr(cm), clo = cm - chi, sc = poly ? 0x1p-71f : 0x1p71f;
      float v0 = 0.f, v1 = 0.f;
      if (k == 0) { v0 = sc; v1 = sc; }
      if (k == 2) { v0 = sc; v1 = poly ? 0.f : chi * sc; }
      if (k == 4) { v0 = poly ? 0.f : clo * sc; }
      *(uint32_t*)(smem + SM_BIAS + n * 32 + (((k >> 3) ^ ((n >> 2) & 1)) << 4) + (k & 7) * 2) = packbf(v0, v1);
    }
    float c0[4] = {0.f, 0.f, 0.f, 0.f}, c1[4] = {0.f, 0.f, 0.f, 0.f};
#pragma unroll
    for (int j = 0; j < 16; j++) {
      float* c = (j & 1) ? c1 : c0;
      asm("mma.sync.aligned.m16n8k16.row.col.f32.bf16.bf16.f32 {%0,%1,%2,%3},{%4,%5,%6,%7},{%8,%8},{%0,%1,%2,%3};"
          : "+f"(c[0]), "+f"(c[1]), "+f"(c[2]), "+f"(c[3]) : "r"(xv[j].x), "r"(xv[j].y), "r"(xv[j].z), "r"(xv[j].w), "r"(0x3F803F80u));
    }
    const float mean = ((c0[0] + c0[2]) + (c1[0] + c1[2])) * (1.f / DM);
    const uint32_t m2 = packbf(mean, mean);
    if (m2 != 0x12345678) TSTAMP(wg, 13);
    const int row = warp * 8 + g;
    if (t == 0) ((float*)(smem + SM_DELTA))[row] = mean - bf_lo(m2);
#pragma unroll
    for (int j = 0; j < 16; j++) {
      const int c = 4 * (j ^ (g & 1)) + t;
      uint4 d;
      d.x = hsub(xv[j].x, m2); d.y = hsub(xv[j].y, m2); d.z = hsub(xv[j].z, m2); d.w = hsub(xv[j].w, m2);
      *(uint4*)(smem + SM_A + (c >> 3) * 16384 + row * 128 + (((c & 7) ^ g) << 4)) = d;
    }
    TSTAMP(wg, 14);
    asm volatile("fence.proxy.async.shared::cta;" ::: "memory");
    bar_sync(1, 544);
  }
  TSTAMP(wg, 1);
  const int pair = wg >> 1, half = wg & 1;
  if (pair == 1) {
#pragma unroll 1
    for (int rr = 0; rr < 2; rr++) {
      const int row = (warp - 8) * 16 + rr * 8 + g;
      float s0 = 0.f, s1 = 0.f, s2 = 0.f, s3 = 0.f;
#pragma unroll 4
      for (int j = 0; j < 16; j++) {
        const int c = 4 * (j ^ (g & 1)) + t;
        const uint4 d = *(const uint4*)(smem + SM_A + (c >> 3) * 16384 + row * 128 + (((c & 7) ^ g) << 4));
        float a;
        a = bf_lo(d.x); s0 = fmaf(a, a, s0); a = bf_hi(d.x); s1 = fmaf(a, a, s1);
        a = bf_lo(d.y); s2 = fmaf(a, a, s2); a = bf_hi(d.y); s3 = fmaf(a, a, s3);
        a = bf_lo(d.z); s0 = fmaf(a, a, s0); a = bf_hi(d.z); s1 = fmaf(a, a, s1);
        a = bf_lo(d.w); s2 = fmaf(a, a, s2); a = bf_hi(d.w); s3 = fmaf(a, a, s3);
      }
      float s = (s0 + s1) + (s2 + s3);
      s += __shfl_xor_sync(~0u, s, 1);
      s += __shfl_xor_sync(~0u, s, 2);
      const float dl = ((const float*)(smem + SM_DELTA))[row];
      const float var = fmaxf(s * (1.f / DM) - dl * dl, 0.f);
      if (t == 0) ((float*)(smem + SM_RSTD))[row] = 1.f / bfr(sqrtf(bfr(bfr(var) + 1e-5f)));
    }
    TSTAMP(wg, 15);
    bar_arrive(2, 512);
    bar_sync(3, 256);
  }

  {
    uint32_t par = 0;
    const uint64_t dA0 = mkdesc(sb + SM_A + half * 8192, 16, 1024, 1), dB0 = mkdesc(sb + SM_RING, 8192, 1024, 1);
#pragma unroll 1
    for (int tI = pair; tI < 5; tI += 2) {
      float acc[64];
      clear<64>(acc);
      int slot = (tI * 8) % NSLOT, prev = 0;
#pragma unroll 1
      for (int k = 0; k < 8; k++) {
        mbar_wait(sb + B_FULL1 + 8 * (pair * NSLOT + slot), (par >> slot) & 1);
        par ^= 1u << slot;
        const uint64_t dA = dA0 + k * 1024, dB = dB0 + slot * 1024;
        wg_fence();
        wg_ss_n128<1>(acc, dA, dB);
        wg_ss_n128<1>(acc, dA + 2, dB + 128);
        wg_ss_n128<1>(acc, dA + 4, dB + 256);
        wg_ss_n128<1>(acc, dA + 6, dB + 384);
        wg_commit();
        if (k > 0) {
          wg_wait<1>();
          if (lane == 0) mbar_arrive(sb + B_EMPTY1 + 8 * prev);
        }
        prev = slot;
        if (++slot == NSLOT) slot = 0;
      }
      wg_wait<0>();
      if (lane == 0) mbar_arrive(sb + B_EMPTY1 + 8 * prev);
      pin<64>(acc);
      TSTAMP(wg, 2 + (tI >> 1) * 2);
      if (tI == 0) bar_sync(2, 512);
      const Tile tl = tile_of(cg, tI);
      const int lrow = half * 64 + w * 16 + g;
      const float r0 = ((const float*)(smem + SM_RSTD))[lrow], r1 = ((const float*)(smem + SM_RSTD))[lrow + 8];
      if (tl.kind == 2) {
        uint32_t* hp = (uint32_t*)(gH + (size_t)((rb * 2 + half) * 28 + (tl.c0 >> 6)) * 8192 + w * 256) + lane;
#pragma unroll
        for (int j = 0; j < 8; j++) {
#pragma unroll
          for (int r = 0; r < 2; r++) {
            const float rs = r ? r1 : r0, e = -LOG2E * rs, q = rs * rs;
            const float g0 = acc[4 * j + 2 * r], g1 = acc[4 * j + 2 * r + 1];
            const float h0 = (g0 * q) * acc[32 + 4 * j + 2 * r] * rcp(1.f + ex2(g0 * e));
            const float h1 = (g1 * q) * acc[33 + 4 * j + 2 * r] * rcp(1.f + ex2(g1 * e));
            hp[j * 256 + r * 32] = packbf(h0, h1);
          }
        }
      } else {
        const int hg = (tl.c0 >> 6) & 7;
#pragma unroll
        for (int u = 0; u < 2; u++) {
#pragma unroll
          for (int r = 0; r < 2; r++) {
            float sc = r ? r1 : r0;
            uint8_t* p;
            size_t hs;
            if (tl.kind == 1) {
              sc *= 0.25f * LOG2E * 0x1p-71f;
              p = gQ + (size_t)(hg + u) * 4 * 65536 + (size_t)(rb * 128 + lrow + r * 8) * 32 + t * 8;
              hs = 65536;
            } else {
              if (u == 0) sc *= ((POLYMASK >> (2 * w + r)) & 1) ? 0x1p-71f : 0x1p71f;
              p = gKV + (size_t)hg * 4 * 131072 + rb * 8192 + u * 4096 + (lrow + r * 8) * 32 + ((t * 8) ^ ((g & 4) << 2));
              hs = 131072;
            }
#pragma unroll
            for (int hh = 0; hh < 4; hh++) {
              const float* a = acc + u * 32 + hh * 8 + 2 * r;
              *(uint2*)(p + hh * hs) = make_uint2(packbf(a[0] * sc, a[1] * sc), packbf(a[4] * sc, a[5] * sc));
            }
          }
        }
      }
      bar_arrive(4 + pair, 288);
      TSTAMP(wg, 3 + (tI >> 1) * 2);
    }
  }

  if (wg < 3) {
    constexpr uint64_t VS = (uint64_t)(32 - (32LL << 16));
    const uint32_t half2 = 0x3F003F00u + zero;
    const uint64_t dBias = mkdesc(sb + SM_BIAS, 16, 256, 3);
    const int nseg = wg == 1 ? 4 : 3;
    for (int j = 0; j < 8; j++) mbar_wait(sb + B_KV + 8 * j, 0);
    TSTAMP(wg, 8);
    bool exact = false;
#pragma unroll 1
    for (int seg = 0; seg < nseg; seg++) {
      int rbl, c0 = 0, c1 = 16, mode = 0;
      if (wg == 1) { rbl = (0x4352 >> (seg * 4)) & 7; if (seg < 2) { c0 = 11; mode = 1; } }
      else { rbl = ((wg ? 0x765 : 0x102) >> (seg * 4)) & 7; if (seg == 0) { c1 = 11; mode = 2; } }
      const int rblk = qb * 8 + rbl;
      uint32_t q[4], qa[4];
      {
        const uint32_t* qp = (const uint32_t*)(gQ + (size_t)head * 65536 + (size_t)(rblk * 64 + w * 16 + g) * 32) + t;
        q[0] = __ldcg(qp); q[1] = __ldcg(qp + 64); q[2] = __ldcg(qp + 4); q[3] = __ldcg(qp + 68);
      }
      const uint32_t va = sb + SM_A + 4096 + c0 * 8192;
      const uint64_t dV0 = mkdesc(va, sb + SM_ONES - va, 256, 3);
      const uint32_t cend = (uint32_t)(dV0 + (uint64_t)(c1 - c0) * 16 * VS);
      float o[12], bias[2];
      {
        const int nmax = exact ? (c1 - c0) * 2 : 1;
        float s[32];
        uint32_t p0[16], p1[16];
        float mp0 = -INFINITY, mp1 = -INFINITY, mm0 = -INFINITY, mm1 = -INFINITY;
#pragma unroll 1
        for (int i = 0; i < nmax; i++) {
          wg_fence();
          wg_rs_n64<0, 0>(s, q, dV0 - 256 + (i >> 1) * 512 + (i & 1) * 128);
          wg_commit();
          wg_wait<0>();
          pin<32>(s);
#pragma unroll
          for (int j = 0; j < 8; j++) {
            if ((POLYMASK >> j) & 1) { mp0 = fmaxf(mp0, fmaxf(s[4 * j], s[4 * j + 1])); mp1 = fmaxf(mp1, fmaxf(s[4 * j + 2], s[4 * j + 3])); }
            else { mm0 = fmaxf(mm0, fmaxf(s[4 * j], s[4 * j + 1])); mm1 = fmaxf(mm1, fmaxf(s[4 * j + 2], s[4 * j + 3])); }
          }
        }
#pragma unroll
        for (int r = 0; r < 2; r++) {
          float v = fmaxf(r ? mm1 : mm0, ((r ? mp1 : mp0) * 0x1p71f) * 0x1p71f);
          v = fmaxf(v, __shfl_xor_sync(~0u, v, 1));
          v = fmaxf(v, __shfl_xor_sync(~0u, v, 2));
          bias[r] = rintf(64.f - v);
          const float y = bias[r] * 0x1p-71f, hi = bfr(y), mid = bfr(y - hi);
          qa[r] = t == 0 ? packbf(hi, mid) : t == 1 ? packbf(y - hi - mid, 0x1p-71f) : t == 2 ? 0x00001C00u : 0u;
          qa[2 + r] = qa[r] & zero;
        }
        clear<12>(o);
        uint64_t c = dV0;
        wg_fence();
        wg_rs_n64<0, 0>(s, qa, dBias);
        wg_rs_n64<0, 1>(s, q, c - 256);
        wg_commit();
        wg_wait<0>();
#pragma unroll 1
        do {
          softmax64(s, p0, half2);
          wg_fence();
          wg_rs_n64<0, 0>(s, qa, dBias);
          wg_rs_n64<0, 1>(s, q, c - 128);
          wg_commit();
#pragma unroll
          for (int k = 0; k < 4; k++) wg_rs_n24<1, 1>(o, p0 + 4 * k, c + k * VS);
          wg_commit();
          wg_wait<1>();
          softmax64(s, p1, half2);
          wg_fence();
          wg_rs_n64<0, 0>(s, qa, dBias);
          wg_rs_n64<0, 1>(s, q, c + 256);
          wg_commit();
#pragma unroll
          for (int k = 0; k < 4; k++) wg_rs_n24<1, 1>(o, p1 + 4 * k, c + (4 + k) * VS);
          wg_commit();
          c += 16 * VS;
          wg_wait<1>();
        } while ((uint32_t)c != cend);
        wg_wait<0>();
        pin<12>(o);
      }
      exact = __all_sync(~0u, bar_or(10 + wg, 128, !exact && !(o[8] < 0x1p90f && o[10] < 0x1p90f)));
      if (exact) { seg--; continue; }
      if (mode == 1) {
        float* mp = (float*)(smem + SM_MERGE + seg * 6144) + (tid & 127);
        o[9] = bias[0]; o[11] = bias[1];
#pragma unroll
        for (int i = 0; i < 12; i++) mp[i * 128] = o[i];
        bar_arrive(8 + seg, 256);
        continue;
      }
      if (mode == 2) {
        const float* mp = (const float*)(smem + SM_MERGE + (wg >> 1) * 6144) + (tid & 127);
        bar_sync(8 + (wg >> 1), 256);
#pragma unroll
        for (int r = 0; r < 2; r++) {
          const float bo = mp[(9 + 2 * r) * 128], bm = fminf(bo, bias[r]);
          const float fa = ex2(0.5f * (bm - bias[r])), fb = ex2(0.5f * (bm - bo));
          o[2 * r] = o[2 * r] * fa * fa + mp[(2 * r) * 128] * fb * fb;
          o[2 * r + 1] = o[2 * r + 1] * fa * fa + mp[(2 * r + 1) * 128] * fb * fb;
          o[4 + 2 * r] = o[4 + 2 * r] * fa * fa + mp[(4 + 2 * r) * 128] * fb * fb;
          o[5 + 2 * r] = o[5 + 2 * r] * fa * fa + mp[(5 + 2 * r) * 128] * fb * fb;
          o[8 + 2 * r] = o[8 + 2 * r] * fa * fa + mp[(8 + 2 * r) * 128] * fb * fb;
        }
      }
      if (seg == nseg - 1 && lane == 0) mbar_arrive(sb + B_ADONE);
#pragma unroll
      for (int r = 0; r < 2; r++) {
        const float inv = rcp(o[8 + 2 * r]);
        const uint32_t a = packbf(o[2 * r] * inv, o[2 * r + 1] * inv), c = packbf(o[4 + 2 * r] * inv, o[5 + 2 * r] * inv);
        const uint32_t e = __shfl_xor_sync(~0u, (t & 2) ? a : c, 2);
        *(uint2*)(gO + (size_t)(rblk * 8 + (head >> 2)) * 8192 + ((head & 3) * 2 + (t & 1)) * 1024 + (2 * w + r) * 128 + g * 16 + (t & 2) * 4) =
            (t & 2) ? make_uint2(e, c) : make_uint2(a, e);
      }
      bar_arrive(13 + wg, 160);
      TSTAMP(wg, 9 + seg);
    }
  } else {
    uint32_t gate[32];
    const uint64_t dB0 = mkdesc(sb + SM_RING, 8192, 1024, 1);
    {
      const uint64_t dA0 = mkdesc(sb + SM_RING + 8192, 1024, 128, 0);
      float acc[64];
      clear<64>(acc);
      int slot = 0;
      uint32_t ph = 0;
#pragma unroll 1
      for (int n = 0; n < 28; n++) {
        mbar_wait(sb + B_FULL2 + 8 * slot, ph);
        const uint64_t dA = dA0 + slot * 1536, dB = dB0 + slot * 1536;
        wg_fence();
#pragma unroll
        for (int k = 0; k < 4; k++) {
          wg_ss_n64<1>(acc, dA + k * 128, dB + k * 128);
          wg_ss_n64<1>(acc + 32, dA + 512 + k * 128, dB + k * 128);
        }
        wg_commit();
        wg_wait<0>();
        if (lane == 0) mbar_arrive(sb + B_EMPTY2 + 8 * slot);
        if (++slot == 3) { slot = 0; ph ^= 1; }
      }
      pin<64>(acc);
#pragma unroll
      for (int i = 0; i < 32; i++) {
        const float f0 = bfr(acc[2 * i]), f1 = bfr(acc[2 * i + 1]);
        gate[i] = packbf(f0 * rcp(1.f + ex2(-LOG2E * f0)), f1 * rcp(1.f + ex2(-LOG2E * f1)));
      }
    }
    TSTAMP(wg, 8);
#pragma unroll
    for (int pass = 0; pass < 2; pass++) {
      const size_t off = (size_t)((pass ? rLate : rEarly) * 64 + w * 16 + g) * DM + cg * 64 + (t & 1) * 8 + (t & 2) * 2;
      uint2 xr[8];
#pragma unroll
      for (int i = 0; i < 8; i++) xr[i] = __ldg((const uint2*)(x + off + (i & 1) * 8 * DM + (i >> 1) * 16));
      float acc[32];
      clear<32>(acc);
      if (pass == 0) {
        const uint64_t dA0 = mkdesc(sb + SM_RING + 65536, 1024, 128, 0);
        mbar_wait(sb + B_WO, 0);
#pragma unroll 1
        for (int n = 0; n < 8; n++) {
          mbar_wait(sb + B_OE + 8 * (n & 1), (n >> 1) & 1);
          wg_fence();
#pragma unroll
          for (int k = 0; k < 4; k++) wg_ss_n64<1>(acc, dA0 + (n & 1) * 512 + k * 128, dB0 + n * 512 + k * 128);
          wg_commit();
          wg_wait<0>();
          if (lane == 0) mbar_arrive(sb + B_OEE + 8 * (n & 1));
        }
      } else {
        mbar_wait(sb + B_ADONE, 0);
        const uint64_t dA = mkdesc(sb + SM_A, 1024, 128, 0);
#pragma unroll 1
        for (int n = 0; n < 4; n++) {
          mbar_wait(sb + B_O + 8 * n, 0);
          wg_fence();
#pragma unroll
          for (int k = 0; k < 8; k++) wg_ss_n64<1>(acc, dA + (n * 8 + k) * 128, dB0 + (n * 8 + k) * 128);
          wg_commit();
        }
        wg_wait<0>();
      }
      pin<32>(acc);
      TSTAMP(wg, 9 + 2 * pass);
#pragma unroll
      for (int i = 0; i < 8; i++) {
        const int ia = (i >> 1) * 4 + (i & 1), ib = ia + 2;
        const uint32_t ya = hmul(packbf(acc[2 * ia], acc[2 * ia + 1]), gate[pass * 16 + ia]);
        const uint32_t yb = hmul(packbf(acc[2 * ib], acc[2 * ib + 1]), gate[pass * 16 + ib]);
        const uint32_t e = __shfl_xor_sync(~0u, (t & 1) ? ya : yb, 1);
        const uint32_t lo = (t & 1) ? e : ya, hi = (t & 1) ? yb : e;
        *(uint2*)(out + off + (i & 1) * 8 * DM + (i >> 1) * 16) = make_uint2(hadd(xr[i].x, lo), hadd(xr[i].y, hi));
      }
      TSTAMP(wg, 10 + 2 * pass);
    }
  }
}

typedef CUresult (*EncodeFn)(CUtensorMap*, CUtensorMapDataType, cuuint32_t, void*, const cuuint64_t*, const cuuint64_t*, const cuuint32_t*,
                             const cuuint32_t*, CUtensorMapInterleave, CUtensorMapSwizzle, CUtensorMapL2promotion, CUtensorMapFloatOOBfill);

void make_map(EncodeFn enc, CUtensorMap* m, void* p, int rows, int cols) {
  const cuuint64_t dims[2] = {(cuuint64_t)cols, (cuuint64_t)rows}, strides[1] = {(cuuint64_t)cols * 2};
  const cuuint32_t box[2] = {64, 64}, es[2] = {1, 1};
  enc(m, CU_TENSOR_MAP_DATA_TYPE_BFLOAT16, 2, p, dims, strides, box, es, CU_TENSOR_MAP_INTERLEAVE_NONE, CU_TENSOR_MAP_SWIZZLE_128B,
      CU_TENSOR_MAP_L2_PROMOTION_L2_128B, CU_TENSOR_MAP_FLOAT_OOB_FILL_NONE);
}

}

extern "C" void kernel_launch(void* const* d_in, const int* in_sizes, int n_in, void* d_out, int out_size) {
  (void)in_sizes; (void)n_in; (void)out_size;
  void* fn = nullptr;
  cudaDriverEntryPointQueryResult qr;
  cudaGetDriverEntryPoint("cuTensorMapEncodeTiled", &fn, cudaEnableDefault, &qr);
  EncodeFn enc = (EncodeFn)fn;
  CUtensorMap mQKV, mW1, mW3, mW2, mWO;
  make_map(enc, &mQKV, d_in[1], DM, 3 * DM);
  make_map(enc, &mWO, d_in[2], DM, DM);
  make_map(enc, &mW1, d_in[4], DM, FF);
  make_map(enc, &mW3, d_in[5], DM, FF);
  make_map(enc, &mW2, d_in[6], FF, DM);
  cudaFuncSetAttribute(fused_kernel, cudaFuncAttributeMaxDynamicSharedMemorySize, SM_TOTAL);
  fused_kernel<<<128, NTHREADS, SM_TOTAL>>>(mQKV, mW1, mW3, mW2, mWO, (const bf16*)d_in[0], (bf16*)d_out, 0u);
}
```

```cpp
#include <cuda_runtime.h>
#include <cuda_bf16.h>
#include <cuda.h>
#include <stdint.h>

namespace {

typedef __nv_bfloat16 bf16;
constexpr int SEQ = 2048, DM = 512, FF = 1792;
constexpr int NTHREADS = 640;
constexpr int NSLOT = 5;
constexpr uint32_t POLYMASK = 0x57;

constexpr uint32_t SM_A     = 0;
constexpr uint32_t SM_RING  = 131072;
constexpr uint32_t SM_ONES  = SM_RING + 81920;
constexpr uint32_t SM_BIAS  = SM_ONES + 512;
constexpr uint32_t SM_MERGE = SM_BIAS + 2048;
constexpr uint32_t SM_RSTD  = SM_MERGE + 12288;
constexpr uint32_t SM_BAR   = SM_RSTD + 512;
constexpr uint32_t B_FULL1  = SM_BAR;
constexpr uint32_t B_EMPTY1 = B_FULL1 + 8 * 2 * NSLOT;
constexpr uint32_t B_KV     = B_EMPTY1 + 8 * NSLOT;
constexpr uint32_t B_FULL2  = B_KV + 64;
constexpr uint32_t B_OE     = B_FULL2 + 24;
constexpr uint32_t B_WO     = B_OE + 16;
constexpr uint32_t B_O      = B_WO + 8;
constexpr uint32_t B_EMPTY2 = B_O + 32;
constexpr uint32_t B_OEE    = B_EMPTY2 + 24;
constexpr uint32_t B_ADONE  = B_OEE + 16;
constexpr uint32_t SM_TOTAL = B_ADONE + 8;

__device__ __align__(1024) uint8_t gQ[32 * SEQ * 32];
__device__ __align__(1024) uint8_t gKV[32 * 16 * 8192];
__device__ __align__(1024) uint8_t gH[32 * 28 * 8192];
__device__ __align__(1024) uint8_t gO[32 * 8 * 8192];
__device__ uint32_t gFlag[72 * 32];
constexpr int F_QKV = 0, F_H = 8, F_O = 40;
#define TSTAMP(role, i)

template<int TB, int SD> __device__ __forceinline__ void wg_rs_n24(float* d, const uint32_t* a, uint64_t db) {
  if (SD)
    asm volatile("wgmma.mma_async.sync.aligned.m64n24k16.f32.bf16.bf16 {%0,%1,%2,%3,%4,%5,%6,%7,%8,%9,%10,%11}, {%12,%13,%14,%15}, %16, 1, 1, 1, %17;"
      : "+f"(d[0]),"+f"(d[1]),"+f"(d[2]),"+f"(d[3]),"+f"(d[4]),"+f"(d[5]),"+f"(d[6]),"+f"(d[7]),"+f"(d[8]),"+f"(d[9]),"+f"(d[10]),"+f"(d[11])
      : "r"(a[0]), "r"(a[1]), "r"(a[2]), "r"(a[3]), "l"(db), "n"(TB));
  else
    asm volatile("wgmma.mma_async.sync.aligned.m64n24k16.f32.bf16.bf16 {%0,%1,%2,%3,%4,%5,%6,%7,%8,%9,%10,%11}, {%12,%13,%14,%15}, %16, 0, 1, 1, %17;"
      : "=f"(d[0]),"=f"(d[1]),"=f"(d[2]),"=f"(d[3]),"=f"(d[4]),"=f"(d[5]),"=f"(d[6]),"=f"(d[7]),"=f"(d[8]),"=f"(d[9]),"=f"(d[10]),"=f"(d[11])
      : "r"(a[0]), "r"(a[1]), "r"(a[2]), "r"(a[3]), "l"(db), "n"(TB));
}
template<int TB, int SD> __device__ __forceinline__ void wg_rs_n64(float* d, const uint32_t* a, uint64_t db) {
  if (SD)
    asm volatile("wgmma.mma_async.sync.aligned.m64n64k16.f32.bf16.bf16 {%0,%1,%2,%3,%4,%5,%6,%7,%8,%9,%10,%11,%12,%13,%14,%15,%16,%17,%18,%19,%20,%21,%22,%23,%24,%25,%26,%27,%28,%29,%30,%31}, {%32,%33,%34,%35}, %36, 1, 1, 1, %37;"
      : "+f"(d[0]),"+f"(d[1]),"+f"(d[2]),"+f"(d[3]),"+f"(d[4]),"+f"(d[5]),"+f"(d[6]),"+f"(d[7]),"+f"(d[8]),"+f"(d[9]),"+f"(d[10]),"+f"(d[11]),"+f"(d[12]),"+f"(d[13]),"+f"(d[14]),"+f"(d[15]),"+f"(d[16]),"+f"(d[17]),"+f"(d[18]),"+f"(d[19]),"+f"(d[20]),"+f"(d[21]),"+f"(d[22]),"+f"(d[23]),"+f"(d[24]),"+f"(d[25]),"+f"(d[26]),"+f"(d[27]),"+f"(d[28]),"+f"(d[29]),"+f"(d[30]),"+f"(d[31])
      : "r"(a[0]), "r"(a[1]), "r"(a[2]), "r"(a[3]), "l"(db), "n"(TB));
  else
    asm volatile("wgmma.mma_async.sync.aligned.m64n64k16.f32.bf16.bf16 {%0,%1,%2,%3,%4,%5,%6,%7,%8,%9,%10,%11,%12,%13,%14,%15,%16,%17,%18,%19,%20,%21,%22,%23,%24,%25,%26,%27,%28,%29,%30,%31}, {%32,%33,%34,%35}, %36, 0, 1, 1, %37;"
      : "=f"(d[0]),"=f"(d[1]),"=f"(d[2]),"=f"(d[3]),"=f"(d[4]),"=f"(d[5]),"=f"(d[6]),"=f"(d[7]),"=f"(d[8]),"=f"(d[9]),"=f"(d[10]),"=f"(d[11]),"=f"(d[12]),"=f"(d[13]),"=f"(d[14]),"=f"(d[15]),"=f"(d[16]),"=f"(d[17]),"=f"(d[18]),"=f"(d[19]),"=f"(d[20]),"=f"(d[21]),"=f"(d[22]),"=f"(d[23]),"=f"(d[24]),"=f"(d[25]),"=f"(d[26]),"=f"(d[27]),"=f"(d[28]),"=f"(d[29]),"=f"(d[30]),"=f"(d[31])
      : "r"(a[0]), "r"(a[1]), "r"(a[2]), "r"(a[3]), "l"(db), "n"(TB));
}
template<int TB> __device__ __forceinline__ void wg_ss_n64(float* d, uint64_t da, uint64_t db) {
  asm volatile("wgmma.mma_async.sync.aligned.m64n64k16.f32.bf16.bf16 {%0,%1,%2,%3,%4,%5,%6,%7,%8,%9,%10,%11,%12,%13,%14,%15,%16,%17,%18,%19,%20,%21,%22,%23,%24,%25,%26,%27,%28,%29,%30,%31}, %32, %33, 1, 1, 1, 0, %34;"
    : "+f"(d[0]),"+f"(d[1]),"+f"(d[2]),"+f"(d[3]),"+f"(d[4]),"+f"(d[5]),"+f"(d[6]),"+f"(d[7]),"+f"(d[8]),"+f"(d[9]),"+f"(d[10]),"+f"(d[11]),"+f"(d[12]),"+f"(d[13]),"+f"(d[14]),"+f"(d[15]),"+f"(d[16]),"+f"(d[17]),"+f"(d[18]),"+f"(d[19]),"+f"(d[20]),"+f"(d[21]),"+f"(d[22]),"+f"(d[23]),"+f"(d[24]),"+f"(d[25]),"+f"(d[26]),"+f"(d[27]),"+f"(d[28]),"+f"(d[29]),"+f"(d[30]),"+f"(d[31])
    : "l"(da), "l"(db), "n"(TB));
}
template<int TB> __device__ __forceinline__ void wg_ss_n128(float* d, uint64_t da, uint64_t db) {
  asm volatile("wgmma.mma_async.sync.aligned.m64n128k16.f32.bf16.bf16 {%0,%1,%2,%3,%4,%5,%6,%7,%8,%9,%10,%11,%12,%13,%14,%15,%16,%17,%18,%19,%20,%21,%22,%23,%24,%25,%26,%27,%28,%29,%30,%31,%32,%33,%34,%35,%36,%37,%38,%39,%40,%41,%42,%43,%44,%45,%46,%47,%48,%49,%50,%51,%52,%53,%54,%55,%56,%57,%58,%59,%60,%61,%62,%63}, %64, %65, 1, 1, 1, 0, %66;"
    : "+f"(d[0]),"+f"(d[1]),"+f"(d[2]),"+f"(d[3]),"+f"(d[4]),"+f"(d[5]),"+f"(d[6]),"+f"(d[7]),"+f"(d[8]),"+f"(d[9]),"+f"(d[10]),"+f"(d[11]),"+f"(d[12]),"+f"(d[13]),"+f"(d[14]),"+f"(d[15]),"+f"(d[16]),"+f"(d[17]),"+f"(d[18]),"+f"(d[19]),"+f"(d[20]),"+f"(d[21]),"+f"(d[22]),"+f"(d[23]),"+f"(d[24]),"+f"(d[25]),"+f"(d[26]),"+f"(d[27]),"+f"(d[28]),"+f"(d[29]),"+f"(d[30]),"+f"(d[31]),"+f"(d[32]),"+f"(d[33]),"+f"(d[34]),"+f"(d[35]),"+f"(d[36]),"+f"(d[37]),"+f"(d[38]),"+f"(d[39]),"+f"(d[40]),"+f"(d[41]),"+f"(d[42]),"+f"(d[43]),"+f"(d[44]),"+f"(d[45]),"+f"(d[46]),"+f"(d[47]),"+f"(d[48]),"+f"(d[49]),"+f"(d[50]),"+f"(d[51]),"+f"(d[52]),"+f"(d[53]),"+f"(d[54]),"+f"(d[55]),"+f"(d[56]),"+f"(d[57]),"+f"(d[58]),"+f"(d[59]),"+f"(d[60]),"+f"(d[61]),"+f"(d[62]),"+f"(d[63])
    : "l"(da), "l"(db), "n"(TB));
}

__device__ __forceinline__ void wg_fence() { asm volatile("wgmma.fence.sync.aligned;" ::: "memory"); }
__device__ __forceinline__ void wg_commit() { asm volatile("wgmma.commit_group.sync.aligned;" ::: "memory"); }
template <int N> __device__ __forceinline__ void wg_wait() { asm volatile("wgmma.wait_group.sync.aligned %0;" ::"n"(N) : "memory"); }
template <int N> __device__ __forceinline__ void pin(float* r) {
#pragma unroll
  for (int i = 0; i < N; i++) asm volatile("" : "+f"(r[i])::"memory");
}
template <int N> __device__ __forceinline__ void clear(float* r) {
#pragma unroll
  for (int i = 0; i < N; i++) r[i] = 0.f;
  pin<N>(r);
}
template <int N> __device__ __forceinline__ void pin(uint32_t* r) {
#pragma unroll
  for (int i = 0; i < N; i++) asm volatile("" : "+r"(r[i])::"memory");
}
__device__ __forceinline__ uint64_t mkdesc(uint32_t addr, uint32_t lbo, uint32_t sbo, uint32_t swz) {
  return (uint64_t)((addr & 0x3FFFF) >> 4) | ((uint64_t)(lbo >> 4) << 16) | ((uint64_t)(sbo >> 4) << 32) | ((uint64_t)swz << 62);
}
__device__ __forceinline__ void mbar_init(uint32_t b, int c) { asm volatile("mbarrier.init.shared::cta.b64 [%0], %1;" ::"r"(b), "r"(c) : "memory"); }
__device__ __forceinline__ void mbar_expect(uint32_t b, int n) { asm volatile("mbarrier.arrive.expect_tx.shared::cta.b64 _, [%0], %1;" ::"r"(b), "r"(n) : "memory"); }
__device__ __forceinline__ void mbar_arrive(uint32_t b) { asm volatile("mbarrier.arrive.shared::cta.b64 _, [%0];" ::"r"(b) : "memory"); }
__device__ __forceinline__ bool mbar_try(uint32_t b, uint32_t ph) {
  uint32_t ok;
  asm volatile("{.reg .pred p; mbarrier.try_wait.parity.shared::cta.b64 p, [%1], %2; selp.u32 %0, 1, 0, p;}" : "=r"(ok) : "r"(b), "r"(ph) : "memory");
  return ok;
}
__device__ __forceinline__ void mbar_wait(uint32_t b, uint32_t ph) {
  if (mbar_try(b, ph)) return;
#pragma unroll 1
  for (int i = 0; i < (1 << 16); i++) {
    uint32_t ok;
    asm volatile("{.reg .pred p; mbarrier.try_wait.parity.shared::cta.b64 p, [%1], %2, 20000; selp.u32 %0, 1, 0, p;}" : "=r"(ok) : "r"(b), "r"(ph) : "memory");
    if (ok) return;
  }
  __trap();
}
__device__ __forceinline__ void bulk_load(uint32_t dst, const void* src, int bytes, uint32_t bar) {
  asm volatile("cp.async.bulk.shared::cluster.global.mbarrier::complete_tx::bytes [%0], [%1], %2, [%3];" ::"r"(dst), "l"(src), "r"(bytes), "r"(bar) : "memory");
}
__device__ __forceinline__ void tma_load(uint32_t dst, const CUtensorMap* m, int c0, int c1, uint32_t bar) {
  asm volatile("cp.async.bulk.tensor.2d.shared::cluster.global.mbarrier::complete_tx::bytes [%0], [%1, {%2, %3}], [%4];" ::"r"(dst), "l"(m), "r"(c0), "r"(c1), "r"(bar) : "memory");
}
__device__ __forceinline__ void tma_prefetch(const CUtensorMap* m, int c0, int c1) {
  asm volatile("cp.async.bulk.prefetch.tensor.2d.L2.global [%0, {%1, %2}];" ::"l"(m), "r"(c0), "r"(c1) : "memory");
}
__device__ __forceinline__ bool elect() {
  uint32_t r;
  asm volatile("{.reg .pred p; elect.sync _|p, 0xffffffff; selp.u32 %0, 1, 0, p;}" : "=r"(r));
  return r;
}
__device__ __forceinline__ void bar_sync(int id, int n) { asm volatile("bar.sync %0, %1;" ::"r"(id), "r"(n) : "memory"); }
__device__ __forceinline__ void bar_arrive(int id, int n) { asm volatile("bar.arrive %0, %1;" ::"r"(id), "r"(n) : "memory"); }
__device__ __forceinline__ bool bar_or(int id, int n, bool v) {
  uint32_t r;
  asm volatile("{.reg .pred p, q; setp.ne.u32 q, %3, 0; bar.red.or.pred p, %1, %2, q; selp.u32 %0, 1, 0, p;}" : "=r"(r) : "r"(id), "r"(n), "r"((uint32_t)v) : "memory");
  return r;
}
__device__ __forceinline__ void flag_add(int f) { asm volatile("red.release.gpu.global.add.u32 [%0], 1;" ::"l"(gFlag + f * 32) : "memory"); }
__device__ __forceinline__ void flag_wait(int f, uint32_t target, uint32_t ns) {
#pragma unroll 1
  for (int i = 0; i < (1 << 22); i++) {
    uint32_t v;
    asm volatile("ld.acquire.gpu.global.u32 %0, [%1];" : "=r"(v) : "l"(gFlag + f * 32) : "memory");
    if ((int)(v - target) >= 0) { asm volatile("fence.proxy.async.global;" ::: "memory"); return; }
    __nanosleep(ns);
  }
  __trap();
}
__device__ __forceinline__ float ex2(float x) { float y; asm("ex2.approx.ftz.f32 %0, %1;" : "=f"(y) : "f"(x)); return y; }
__device__ __forceinline__ float rcp(float x) { float y; asm("rcp.approx.ftz.f32 %0, %1;" : "=f"(y) : "f"(x)); return y; }
__device__ __forceinline__ uint32_t packbf(float lo, float hi) { uint32_t d; asm("cvt.rn.bf16x2.f32 %0, %1, %2;" : "=r"(d) : "f"(hi), "f"(lo)); return d; }
__device__ __forceinline__ float bfr(float x) { return __bfloat162float(__float2bfloat16(x)); }
__device__ __forceinline__ float bf_lo(uint32_t u) { return __uint_as_float(u << 16); }
__device__ __forceinline__ float bf_hi(uint32_t u) { return __uint_as_float(u & 0xFFFF0000u); }
__device__ __forceinline__ uint32_t hmul(uint32_t a, uint32_t b) { uint32_t d; asm("mul.rn.bf16x2 %0, %1, %2;" : "=r"(d) : "r"(a), "r"(b)); return d; }
__device__ __forceinline__ uint32_t hadd(uint32_t a, uint32_t b) { uint32_t d; asm("add.rn.bf16x2 %0, %1, %2;" : "=r"(d) : "r"(a), "r"(b)); return d; }
__device__ __forceinline__ uint32_t hsub(uint32_t a, uint32_t b) { uint32_t d; asm("sub.rn.bf16x2 %0, %1, %2;" : "=r"(d) : "r"(a), "r"(b)); return d; }
__device__ __forceinline__ void hmma(float* c, const uint4& a, uint32_t b0, uint32_t b1) {
  asm("mma.sync.aligned.m16n8k16.row.col.f32.bf16.bf16.f32 {%0,%1,%2,%3},{%4,%5,%6,%7},{%8,%9},{%0,%1,%2,%3};"
      : "+f"(c[0]), "+f"(c[1]), "+f"(c[2]), "+f"(c[3]) : "r"(a.x), "r"(a.y), "r"(a.z), "r"(a.w), "r"(b0), "r"(b1));
}
constexpr float LOG2E = 1.4426950408889634f;

__device__ __forceinline__ uint32_t exp_poly(float lo, float hi, uint32_t half2) {
  uint32_t u, mh, p;
  asm("cvt.pack.sat.s16.s32 %0, %1, %2;" : "=r"(u) : "r"(__float_as_uint(hi)), "r"(__float_as_uint(lo)));
  asm("lop3.b32 %0, %1, 0x007F007F, %2, 0xEA;" : "=r"(mh) : "r"(u), "r"(half2));
  asm("fma.rn.bf16x2 %0, %1, %2, %3;" : "=r"(p) : "r"(u), "r"(mh), "r"(u & 0xFF80FF80u));
  return p;
}
__device__ __forceinline__ void softmax64(float* s, uint32_t* p, uint32_t half2) {
  pin<32>(s);
#pragma unroll
  for (int j = 0; j < 8; j++) {
#pragma unroll
    for (int r = 0; r < 2; r++) {
      const float a = s[4 * j + 2 * r], b = s[4 * j + 2 * r + 1];
      p[2 * j + r] = ((POLYMASK >> j) & 1) ? exp_poly(a, b, half2) : packbf(ex2(a), ex2(b));
    }
  }
  pin<16>(p);
}

struct Tile { int kind, c0, c1; };
__device__ __forceinline__ Tile tile_of(int cg, int t) {
  const int c2 = cg >> 1;
  Tile r;
  if (cg & 1) {
    if (t == 0) { r.kind = 1; r.c0 = c2 * 128; r.c1 = r.c0 + 64; }
    else { r.kind = 2; r.c0 = r.c1 = (7 * c2 + 2 + t) * 64; }
  } else {
    if (t < 2) { r.kind = 0; r.c0 = 512 + c2 * 128 + t * 64; r.c1 = r.c0 + 512; }
    else { r.kind = 2; r.c0 = r.c1 = (7 * c2 + t - 2) * 64; }
  }
  return r;
}

__global__ void __launch_bounds__(NTHREADS, 1)
fused_kernel(const __grid_constant__ CUtensorMap mQKV, const __grid_constant__ CUtensorMap mW1, const __grid_constant__ CUtensorMap mW3,
             const __grid_constant__ CUtensorMap mW2, const __grid_constant__ CUtensorMap mWO, const bf16* __restrict__ x, bf16* __restrict__ out,
             uint32_t zero) {
  extern __shared__ __align__(1024) uint8_t smem[];
  const uint32_t sb = (uint32_t)__cvta_generic_to_shared(smem);
  const int tid = threadIdx.x, lane = tid & 31, g = lane >> 2, t = lane & 3;
  const int warp = __shfl_sync(~0u, tid >> 5, 0), wg = warp >> 2, w = warp & 3;
  const int b = blockIdx.x;
  const int rb = b >> 3, cg = b & 7;
  const int head = b & 31, qb = b >> 5;
  const int rEarly = (rb >> 2) * 8 + ((0x3052 >> ((rb & 3) * 4)) & 7), rLate = (rb >> 2) * 8 + ((0x6741 >> ((rb & 3) * 4)) & 7);

  if (wg == 4) {
    asm volatile("setmaxnreg.dec.sync.aligned.u32 32;");
    if (w == 0) {
      uint32_t epoch;
      asm volatile("ld.relaxed.gpu.global.u32 %0, [%1];" : "=r"(epoch) : "l"(gFlag + F_O * 32) : "memory");
      if (lane < 2 * NSLOT) mbar_init(sb + B_FULL1 + 8 * lane, 1);
      if (lane < NSLOT) mbar_init(sb + B_EMPTY1 + 8 * lane, 8);
      if (lane < 24) mbar_init(sb + B_KV + 8 * lane, lane < 18 ? 1 : lane < 23 ? 4 : 12);
      asm volatile("fence.mbarrier_init.release.cluster;" ::: "memory");
      asm volatile("fence.proxy.async.shared::cta;" ::: "memory");
      __syncwarp();
      bar_arrive(1, 544);
      epoch = (epoch >> 5) + 1;
      int slot = 0;
      uint32_t ph = 1;
#pragma unroll 1
      for (int tI = 0; tI < 5; tI++) {
        const Tile tl = tile_of(cg, tI);
        const CUtensorMap *m0 = tl.kind == 2 ? &mW1 : &mQKV, *m1 = tl.kind == 2 ? &mW3 : &mQKV;
#pragma unroll 1
        for (int k = 0; k < 8; k++) {
          const uint32_t full = sb + B_FULL1 + 8 * ((tI & 1) * NSLOT + slot), dst = sb + SM_RING + slot * 16384;
          if (tI == 0 && k == 2) bar_sync(2, 544);
          if (tI == 4 && k == 0) flag_wait(F_QKV + (head >> 2), epoch * 32, 32);
          if (tI == 0 && k == NSLOT) {
            const int i = 2 * NSLOT + rb + lane * 16;
            if (i < 80) {
              const Tile tp = tile_of(cg, i >> 4);
              tma_prefetch((i & 1) ? (tp.kind == 2 ? &mW3 : &mQKV) : (tp.kind == 2 ? &mW1 : &mQKV), (i & 1) ? tp.c1 : tp.c0, ((i >> 1) & 7) * 64);
            }
            __syncwarp();
          }
          mbar_wait(sb + B_EMPTY1 + 8 * slot, ph);
          if (elect()) {
            mbar_expect(full, 16384);
            tma_load(dst, m0, tl.c0, k * 64, full);
            tma_load(dst + 8192, m1, tl.c1, k * 64, full);
          }
          if (++slot == NSLOT) { slot = 0; ph ^= 1; }
        }
      }
#pragma unroll 1
      for (int j = 0; j < 8; j++) {
        if (j >= 8 - NSLOT) {
          mbar_wait(sb + B_EMPTY1 + 8 * slot, ph);
          if (++slot == NSLOT) { slot = 0; ph ^= 1; }
        }
        if (elect()) {
          mbar_expect(sb + B_KV + 8 * j, 16384);
          bulk_load(sb + SM_A + j * 16384, gKV + (size_t)head * 131072 + j * 16384, 16384, sb + B_KV + 8 * j);
        }
      }
      flag_wait(F_H + rEarly, epoch * 28, 100);
      flag_wait(F_H + rLate, epoch * 28, 100);
      slot = 0; ph = 1;
#pragma unroll 1
      for (int n = 0; n < 31; n++) {
        const uint32_t full = sb + B_FULL2 + 8 * slot, dst = sb + SM_RING + slot * 24576;
        mbar_wait(sb + B_EMPTY2 + 8 * slot, ph);
        if (n < 28 && elect()) {
          mbar_expect(full, 24576);
          tma_load(dst, &mW2, cg * 64, n * 64, full);
          bulk_load(dst + 8192, gH + (size_t)(rEarly * 28 + n) * 8192, 8192, full);
          bulk_load(dst + 16384, gH + (size_t)(rLate * 28 + n) * 8192, 8192, full);
        }
        if (++slot == 3) { slot = 0; ph ^= 1; }
      }
      if (elect()) {
        mbar_expect(sb + B_WO, 65536);
#pragma unroll 1
        for (int k = 0; k < 8; k++) tma_load(sb + SM_RING + k * 8192, &mWO, cg * 64, k * 64, sb + B_WO);
      }
      flag_wait(F_O + rEarly, epoch * 32, 200);
#pragma unroll 1
      for (int n = 0; n < 8; n++) {
        mbar_wait(sb + B_OEE + 8 * (n & 1), ((n >> 1) & 1) ^ 1);
        if (elect()) {
          mbar_expect(sb + B_OE + 8 * (n & 1), 8192);
          bulk_load(sb + SM_RING + 65536 + (n & 1) * 8192, gO + (size_t)(rEarly * 8 + n) * 8192, 8192, sb + B_OE + 8 * (n & 1));
        }
      }
      mbar_wait(sb + B_ADONE, 0);
      flag_wait(F_O + rLate, epoch * 32, 20);
      if (elect()) {
#pragma unroll
        for (int i = 0; i < 4; i++) {
          mbar_expect(sb + B_O + 8 * i, 16384);
          bulk_load(sb + SM_A + i * 16384, gO + (size_t)rLate * 65536 + i * 16384, 16384, sb + B_O + 8 * i);
        }
      }
    } else {
      if (w < 3) {
#pragma unroll 1
        for (int tI = w - 1; tI < 5; tI += 2) {
          const Tile tl = tile_of(cg, tI);
          bar_sync(3 + w, 288);
          if (lane < (tl.kind ? 2 : 1)) flag_add(tl.kind == 2 ? F_H + rb * 2 + lane : F_QKV + ((tl.c0 >> 6) & 7) + lane);
          __syncwarp();
        }
      }
#pragma unroll 1
      for (int i = 0; i < (w == 2 ? 2 : 3); i++) {
        bar_sync(12 + w, 160);
        if (lane == 0) flag_add(F_O + qb * 8 + (((w == 1 ? 0x102 : w == 2 ? 0x43 : 0x765) >> (i * 4)) & 7));
        __syncwarp();
      }
    }
    return;
  }

  TSTAMP(wg, 0);
  uint4 xv[16];
  {
    const uint4* xp = (const uint4*)(x + (size_t)(rb * 128 + warp * 8 + g) * DM);
#pragma unroll
    for (int j = 0; j < 16; j++) xv[j] = __ldg(xp + 4 * (j ^ (g & 1)) + t);
  }
  asm volatile("setmaxnreg.inc.sync.aligned.u32 112;");

  {
    if (tid < 128) ((uint32_t*)(smem + SM_ONES))[tid] = 0x3F803F80u;
    {
      const int n = tid >> 3, k = (tid & 7) * 2;
      const bool poly = (POLYMASK >> (n >> 3)) & 1;
      const float cm = -127.f + 0.5849625f - 0.0020f, chi = bfr(cm), clo = cm - chi, sc = poly ? 0x1p-71f : 0x1p71f;
      float v0 = 0.f, v1 = 0.f;
      if (k == 0) { v0 = sc; v1 = sc; }
      if (k == 2) { v0 = sc; v1 = poly ? 0.f : chi * sc; }
      if (k == 4) { v0 = poly ? 0.f : clo * sc; }
      *(uint32_t*)(smem + SM_BIAS + n * 32 + (((k >> 3) ^ ((n >> 2) & 1)) << 4) + (k & 7) * 2) = packbf(v0, v1);
    }
    float cs[4] = {0.f, 0.f, 0.f, 0.f}, ca[4] = {0.f, 0.f, 0.f, 0.f}, cb[4] = {0.f, 0.f, 0.f, 0.f};
#pragma unroll
    for (int j = 0; j < 16; j++) {
      hmma(cs, xv[j], 0x3F803F80u, 0x3F803F80u);
      hmma(ca, xv[j], xv[j].x, xv[j].z);
      hmma(cb, xv[j], xv[j].y, xv[j].w);
    }
    bar_arrive(2, 544);
    const float mean = (cs[0] + cs[2]) * (1.f / DM);
    const uint32_t m2 = packbf(mean, mean);
    if (m2 != 0x12345678) TSTAMP(wg, 13);
    const int row = warp * 8 + g;
    if (t == (g >> 1)) {
      const float var = fmaxf(((g & 1) ? ca[1] + cb[3] : ca[0] + cb[2]) * (1.f / DM) - mean * mean, 0.f);
      ((float*)(smem + SM_RSTD))[row] = 1.f / bfr(sqrtf(bfr(bfr(var) + 1e-5f)));
    }
#pragma unroll
    for (int j = 0; j < 16; j++) {
      const int c = 4 * (j ^ (g & 1)) + t;
      uint4 d;
      d.x = hsub(xv[j].x, m2); d.y = hsub(xv[j].y, m2); d.z = hsub(xv[j].z, m2); d.w = hsub(xv[j].w, m2);
      *(uint4*)(smem + SM_A + (c >> 3) * 16384 + row * 128 + (((c & 7) ^ g) << 4)) = d;
    }
    TSTAMP(wg, 14);
    asm volatile("fence.proxy.async.shared::cta;" ::: "memory");
    bar_sync(1, 544);
  }
  TSTAMP(wg, 1);
  const int pair = wg >> 1, half = wg & 1;

  {
    uint32_t par = 0;
    const uint64_t dA0 = mkdesc(sb + SM_A + half * 8192, 16, 1024, 1), dB0 = mkdesc(sb + SM_RING, 8192, 1024, 1);
#pragma unroll 1
    for (int tI = pair; tI < 5; tI += 2) {
      float acc[64];
      clear<64>(acc);
      int slot = (tI * 8) % NSLOT, prev = 0;
#pragma unroll 1
      for (int k = 0; k < 8; k++) {
        mbar_wait(sb + B_FULL1 + 8 * (pair * NSLOT + slot), (par >> slot) & 1);
        par ^= 1u << slot;
        const uint64_t dA = dA0 + k * 1024, dB = dB0 + slot * 1024;
        wg_fence();
        wg_ss_n128<1>(acc, dA, dB);
        wg_ss_n128<1>(acc, dA + 2, dB + 128);
        wg_ss_n128<1>(acc, dA + 4, dB + 256);
        wg_ss_n128<1>(acc, dA + 6, dB + 384);
        wg_commit();
        if (k > 0) {
          wg_wait<1>();
          if (lane == 0) mbar_arrive(sb + B_EMPTY1 + 8 * prev);
        }
        prev = slot;
        if (++slot == NSLOT) slot = 0;
      }
      wg_wait<0>();
      if (lane == 0) mbar_arrive(sb + B_EMPTY1 + 8 * prev);
      pin<64>(acc);
      TSTAMP(wg, 2 + (tI >> 1) * 2);
      const Tile tl = tile_of(cg, tI);
      const int lrow = half * 64 + w * 16 + g;
      const float r0 = ((const float*)(smem + SM_RSTD))[lrow], r1 = ((const float*)(smem + SM_RSTD))[lrow + 8];
      if (tl.kind == 2) {
        uint32_t* hp = (uint32_t*)(gH + (size_t)((rb * 2 + half) * 28 + (tl.c0 >> 6)) * 8192 + w * 256) + lane;
#pragma unroll
        for (int j = 0; j < 8; j++) {
#pragma unroll
          for (int r = 0; r < 2; r++) {
            const float rs = r ? r1 : r0, e = -LOG2E * rs, q = rs * rs;
            const float g0 = acc[4 * j + 2 * r], g1 = acc[4 * j + 2 * r + 1];
            const float h0 = (g0 * q) * acc[32 + 4 * j + 2 * r] * rcp(1.f + ex2(g0 * e));
            const float h1 = (g1 * q) * acc[33 + 4 * j + 2 * r] * rcp(1.f + ex2(g1 * e));
            hp[j * 256 + r * 32] = packbf(h0, h1);
          }
        }
      } else {
        const int hg = (tl.c0 >> 6) & 7;
#pragma unroll
        for (int u = 0; u < 2; u++) {
#pragma unroll
          for (int r = 0; r < 2; r++) {
            float sc = r ? r1 : r0;
            uint8_t* p;
            size_t hs;
            if (tl.kind == 1) {
              sc *= 0.25f * LOG2E * 0x1p-71f;
              p = gQ + (size_t)(hg + u) * 4 * 65536 + (size_t)(rb * 128 + lrow + r * 8) * 32 + t * 8;
              hs = 65536;
            } else {
              if (u == 0) sc *= ((POLYMASK >> (2 * w + r)) & 1) ? 0x1p-71f : 0x1p71f;
              p = gKV + (size_t)hg * 4 * 131072 + rb * 8192 + u * 4096 + (lrow + r * 8) * 32 + ((t * 8) ^ ((g & 4) << 2));
              hs = 131072;
            }
#pragma unroll
            for (int hh = 0; hh < 4; hh++) {
              const float* a = acc + u * 32 + hh * 8 + 2 * r;
              *(uint2*)(p + hh * hs) = make_uint2(packbf(a[0] * sc, a[1] * sc), packbf(a[4] * sc, a[5] * sc));
            }
          }
        }
      }
      bar_arrive(4 + pair, 288);
      TSTAMP(wg, 3 + (tI >> 1) * 2);
    }
  }

  if (wg < 3) {
    constexpr uint64_t VS = (uint64_t)(32 - (32LL << 16));
    const uint32_t half2 = 0x3F003F00u + zero;
    const uint64_t dBias = mkdesc(sb + SM_BIAS, 16, 256, 3);
    const int nseg = wg == 1 ? 4 : 3;
    const uint32_t segs = wg == 0 ? 0x102 : wg == 1 ? 0x4352 : 0x765;
    int ready = wg == 0 ? 2 : 0;
    mbar_wait(sb + B_KV + 8 * ready, 0);
    const uint8_t* qbase = gQ + (size_t)head * 65536 + (size_t)(qb * 512 + w * 16) * 32;
    if (lane < 4 * nseg) asm volatile("prefetch.global.L1 [%0];" ::"l"(qbase + ((segs >> (lane & ~3)) & 7) * 2048 + (lane & 3) * 128));
    TSTAMP(wg, 8);
    bool exact = false;
#pragma unroll 1
    for (int seg = 0; seg < nseg; seg++) {
      int c0 = 0, c1 = 16, mode = 0;
      if (wg == 1) { if (seg < 2) { c0 = seg * 11; c1 = c0 + 5; mode = 1; } }
      else if (seg == 0) { c0 = wg ? 0 : 5; c1 = c0 + 11; mode = 2; }
      const int rbl = (segs >> (seg * 4)) & 7, rblk = qb * 8 + rbl;
      if (seg > 0 || exact) {
#pragma unroll 1
        for (int j = 0; j < 8; j++) mbar_wait(sb + B_KV + 8 * j, 0);
        ready = 7;
      }
      uint32_t q[4], qa[4];
      {
        const uint32_t* qp = (const uint32_t*)(qbase + rbl * 2048 + g * 32) + t;
        q[0] = __ldca(qp); q[1] = __ldca(qp + 64); q[2] = __ldca(qp + 4); q[3] = __ldca(qp + 68);
      }
      const uint32_t va = sb + SM_A + 4096 + c0 * 8192;
      const uint64_t dV0 = mkdesc(va, sb + SM_ONES - va, 256, 3);
      float o[12], bias[2];
      {
        const int nmax = exact ? (c1 - c0) * 2 : 1;
        float s[32];
        uint32_t p0[16], p1[16];
        float mp0 = -INFINITY, mp1 = -INFINITY, mm0 = -INFINITY, mm1 = -INFINITY;
#pragma unroll 1
        for (int i = 0; i < nmax; i++) {
          wg_fence();
          wg_rs_n64<0, 0>(s, q, dV0 - 256 + (i >> 1) * 512 + (i & 1) * 128);
          wg_commit();
          wg_wait<0>();
          pin<32>(s);
#pragma unroll
          for (int j = 0; j < 8; j++) {
            if ((POLYMASK >> j) & 1) { mp0 = fmaxf(mp0, fmaxf(s[4 * j], s[4 * j + 1])); mp1 = fmaxf(mp1, fmaxf(s[4 * j + 2], s[4 * j + 3])); }
            else { mm0 = fmaxf(mm0, fmaxf(s[4 * j], s[4 * j + 1])); mm1 = fmaxf(mm1, fmaxf(s[4 * j + 2], s[4 * j + 3])); }
          }
        }
#pragma unroll
        for (int r = 0; r < 2; r++) {
          float v = fmaxf(r ? mm1 : mm0, ((r ? mp1 : mp0) * 0x1p71f) * 0x1p71f);
          v = fmaxf(v, __shfl_xor_sync(~0u, v, 1));
          v = fmaxf(v, __shfl_xor_sync(~0u, v, 2));
          bias[r] = rintf(64.f - v);
          const float y = bias[r] * 0x1p-71f, hi = bfr(y), mid = bfr(y - hi);
          qa[r] = t == 0 ? packbf(hi, mid) : t == 1 ? packbf(y - hi - mid, 0x1p-71f) : t == 2 ? 0x00001C00u : 0u;
          qa[2 + r] = qa[r] & zero;
        }
        clear<12>(o);
        uint64_t c = dV0;
        wg_fence();
        wg_rs_n64<0, 0>(s, qa, dBias);
        wg_rs_n64<0, 1>(s, q, c - 256);
        wg_commit();
        wg_wait<0>();
        if (seg == nseg - 1) TSTAMP(wg, 15);
#pragma unroll 1
        for (int ci = c0; ci < c1;) {
        if (ready < 7) mbar_wait(sb + B_KV + 8 * ++ready, 0);
        ci = ready == 7 ? c1 : min(c1, 2 * ready);
        const uint32_t cend = (uint32_t)(dV0 + (uint64_t)(ci - c0) * 16 * VS);
#pragma unroll 1
        do {
          softmax64(s, p0, half2);
          wg_fence();
          wg_rs_n64<0, 0>(s, qa, dBias);
          wg_rs_n64<0, 1>(s, q, c - 128);
          wg_commit();
#pragma unroll
          for (int k = 0; k < 4; k++) wg_rs_n24<1, 1>(o, p0 + 4 * k, c + k * VS);
          wg_commit();
          wg_wait<1>();
          softmax64(s, p1, half2);
          wg_fence();
          wg_rs_n64<0, 0>(s, qa, dBias);
          wg_rs_n64<0, 1>(s, q, c + 256);
          wg_commit();
#pragma unroll
          for (int k = 0; k < 4; k++) wg_rs_n24<1, 1>(o, p1 + 4 * k, c + (4 + k) * VS);
          wg_commit();
          c += 16 * VS;
          wg_wait<1>();
        } while ((uint32_t)c != cend);
        }
        wg_wait<0>();
        pin<12>(o);
      }
      exact = __all_sync(~0u, bar_or(10 + wg, 128, !exact && !(o[8] < 0x1p90f && o[10] < 0x1p90f)));
      if (exact) { seg--; continue; }
      if (mode == 1) {
        float* mp = (float*)(smem + SM_MERGE + seg * 6144) + (tid & 127);
        o[9] = bias[0]; o[11] = bias[1];
#pragma unroll
        for (int i = 0; i < 12; i++) mp[i * 128] = o[i];
        bar_arrive(8 + seg, 256);
        continue;
      }
      if (mode == 2) {
        const float* mp = (const float*)(smem + SM_MERGE + (wg >> 1) * 6144) + (tid & 127);
        bar_sync(8 + (wg >> 1), 256);
#pragma unroll
        for (int r = 0; r < 2; r++) {
          const float bo = mp[(9 + 2 * r) * 128], bm = fminf(bo, bias[r]);
          const float fa = ex2(0.5f * (bm - bias[r])), fb = ex2(0.5f * (bm - bo));
          o[2 * r] = o[2 * r] * fa * fa + mp[(2 * r) * 128] * fb * fb;
          o[2 * r + 1] = o[2 * r + 1] * fa * fa + mp[(2 * r + 1) * 128] * fb * fb;
          o[4 + 2 * r] = o[4 + 2 * r] * fa * fa + mp[(4 + 2 * r) * 128] * fb * fb;
          o[5 + 2 * r] = o[5 + 2 * r] * fa * fa + mp[(5 + 2 * r) * 128] * fb * fb;
          o[8 + 2 * r] = o[8 + 2 * r] * fa * fa + mp[(8 + 2 * r) * 128] * fb * fb;
        }
      }
      if (seg == nseg - 1 && lane == 0) mbar_arrive(sb + B_ADONE);
#pragma unroll
      for (int r = 0; r < 2; r++) {
        const float inv = rcp(o[8 + 2 * r]);
        const uint32_t a = packbf(o[2 * r] * inv, o[2 * r + 1] * inv), c = packbf(o[4 + 2 * r] * inv, o[5 + 2 * r] * inv);
        const uint32_t e = __shfl_xor_sync(~0u, (t & 2) ? a : c, 2);
        *(uint2*)(gO + (size_t)(rblk * 8 + (head >> 2)) * 8192 + ((head & 3) * 2 + (t & 1)) * 1024 + (2 * w + r) * 128 + g * 16 + (t & 2) * 4) =
            (t & 2) ? make_uint2(e, c) : make_uint2(a, e);
      }
      bar_arrive(13 + wg, 160);
      TSTAMP(wg, 9 + seg);
    }
  } else {
    uint32_t gate[32];
    const uint64_t dB0 = mkdesc(sb + SM_RING, 8192, 1024, 1);
    {
      const uint64_t dA0 = mkdesc(sb + SM_RING + 8192, 1024, 128, 0);
      float acc[64];
      clear<64>(acc);
      int slot = 0;
      uint32_t ph = 0;
#pragma unroll 1
      for (int n = 0; n < 28; n++) {
        mbar_wait(sb + B_FULL2 + 8 * slot, ph);
        const uint64_t dA = dA0 + slot * 1536, dB = dB0 + slot * 1536;
        wg_fence();
#pragma unroll
        for (int k = 0; k < 4; k++) {
          wg_ss_n64<1>(acc, dA + k * 128, dB + k * 128);
          wg_ss_n64<1>(acc + 32, dA + 512 + k * 128, dB + k * 128);
        }
        wg_commit();
        wg_wait<0>();
        if (lane == 0) mbar_arrive(sb + B_EMPTY2 + 8 * slot);
        if (++slot == 3) { slot = 0; ph ^= 1; }
      }
      pin<64>(acc);
#pragma unroll
      for (int i = 0; i < 32; i++) {
        const float f0 = bfr(acc[2 * i]), f1 = bfr(acc[2 * i + 1]);
        gate[i] = packbf(f0 * rcp(1.f + ex2(-LOG2E * f0)), f1 * rcp(1.f + ex2(-LOG2E * f1)));
      }
    }
    TSTAMP(wg, 8);
#pragma unroll
    for (int pass = 0; pass < 2; pass++) {
      const size_t off = (size_t)((pass ? rLate : rEarly) * 64 + w * 16 + g) * DM + cg * 64 + (t & 1) * 8 + (t & 2) * 2;
      uint2 xr[8];
#pragma unroll
      for (int i = 0; i < 8; i++) xr[i] = __ldg((const uint2*)(x + off + (i & 1) * 8 * DM + (i >> 1) * 16));
      float acc[32];
      clear<32>(acc);
      if (pass == 0) {
        const uint64_t dA0 = mkdesc(sb + SM_RING + 65536, 1024, 128, 0);
        mbar_wait(sb + B_WO, 0);
#pragma unroll 1
        for (int n = 0; n < 8; n++) {
          mbar_wait(sb + B_OE + 8 * (n & 1), (n >> 1) & 1);
          wg_fence();
#pragma unroll
          for (int k = 0; k < 4; k++) wg_ss_n64<1>(acc, dA0 + (n & 1) * 512 + k * 128, dB0 + n * 512 + k * 128);
          wg_commit();
          wg_wait<0>();
          if (lane == 0) mbar_arrive(sb + B_OEE + 8 * (n & 1));
        }
      } else {
        mbar_wait(sb + B_ADONE, 0);
        const uint64_t dA = mkdesc(sb + SM_A, 1024, 128, 0);
#pragma unroll 1
        for (int n = 0; n < 4; n++) {
          mbar_wait(sb + B_O + 8 * n, 0);
          wg_fence();
#pragma unroll
          for (int k = 0; k < 8; k++) wg_ss_n64<1>(acc, dA + (n * 8 + k) * 128, dB0 + (n * 8 + k) * 128);
          wg_commit();
        }
        wg_wait<0>();
      }
      pin<32>(acc);
      TSTAMP(wg, 9 + 2 * pass);
#pragma unroll
      for (int i = 0; i < 8; i++) {
        const int ia = (i >> 1) * 4 + (i & 1), ib = ia + 2;
        const uint32_t ya = hmul(packbf(acc[2 * ia], acc[2 * ia + 1]), gate[pass * 16 + ia]);
        const uint32_t yb = hmul(packbf(acc[2 * ib], acc[2 * ib + 1]), gate[pass * 16 + ib]);
        const uint32_t e = __shfl_xor_sync(~0u, (t & 1) ? ya : yb, 1);
        const uint32_t lo = (t & 1) ? e : ya, hi = (t & 1) ? yb : e;
        *(uint2*)(out + off + (i & 1) * 8 * DM + (i >> 1) * 16) = make_uint2(hadd(xr[i].x, lo), hadd(xr[i].y, hi));
      }
      TSTAMP(wg, 10 + 2 * pass);
    }
  }
}

typedef CUresult (*EncodeFn)(CUtensorMap*, CUtensorMapDataType, cuuint32_t, void*, const cuuint64_t*, const cuuint64_t*, const cuuint32_t*,
                             const cuuint32_t*, CUtensorMapInterleave, CUtensorMapSwizzle, CUtensorMapL2promotion, CUtensorMapFloatOOBfill);

void make_map(EncodeFn enc, CUtensorMap* m, void* p, int rows, int cols) {
  const cuuint64_t dims[2] = {(cuuint64_t)cols, (cuuint64_t)rows}, strides[1] = {(cuuint64_t)cols * 2};
  const cuuint32_t box[2] = {64, 64}, es[2] = {1, 1};
  enc(m, CU_TENSOR_MAP_DATA_TYPE_BFLOAT16, 2, p, dims, strides, box, es, CU_TENSOR_MAP_INTERLEAVE_NONE, CU_TENSOR_MAP_SWIZZLE_128B,
      CU_TENSOR_MAP_L2_PROMOTION_L2_128B, CU_TENSOR_MAP_FLOAT_OOB_FILL_NONE);
}

}

extern "C" void kernel_launch(void* const* d_in, const int* in_sizes, int n_in, void* d_out, int out_size) {
  (void)in_sizes; (void)n_in; (void)out_size;
  void* fn = nullptr;
  cudaDriverEntryPointQueryResult qr;
  cudaGetDriverEntryPoint("cuTensorMapEncodeTiled", &fn, cudaEnableDefault, &qr);
  EncodeFn enc = (EncodeFn)fn;
  CUtensorMap mQKV, mW1, mW3, mW2, mWO;
  make_map(enc, &mQKV, d_in[1], DM, 3 * DM);
  make_map(enc, &mWO, d_in[2], DM, DM);
  make_map(enc, &mW1, d_in[4], DM, FF);
  make_map(enc, &mW3, d_in[5], DM, FF);
  make_map(enc, &mW2, d_in[6], FF, DM);
  cudaFuncSetAttribute(fused_kernel, cudaFuncAttributeMaxDynamicSharedMemorySize, SM_TOTAL);
  fused_kernel<<<128, NTHREADS, SM_TOTAL>>>(mQKV, mW1, mW3, mW2, mWO, (const bf16*)d_in[0], (bf16*)d_out, 0u);
}
```

```cpp
#include <cuda_runtime.h>
#include <cuda_bf16.h>
#include <cuda.h>
#include <stdint.h>

namespace {

typedef __nv_bfloat16 bf16;
constexpr int SEQ = 2048, DM = 512, FF = 1792;
constexpr int NTHREADS = 640;
constexpr int NSLOT = 5;
constexpr uint32_t POLYMASK = 0x57;

constexpr uint32_t SM_A     = 0;
constexpr uint32_t SM_RING  = 131072;
constexpr uint32_t SM_ONES  = SM_RING + 81920;
constexpr uint32_t SM_BIAS  = SM_ONES + 512;
constexpr uint32_t SM_MERGE = SM_BIAS + 2048;
constexpr uint32_t SM_RSTD  = SM_MERGE + 12288;
constexpr uint32_t SM_BAR   = SM_RSTD + 512;
constexpr uint32_t B_FULL1  = SM_BAR;
constexpr uint32_t B_EMPTY1 = B_FULL1 + 8 * 2 * NSLOT;
constexpr uint32_t B_KV     = B_EMPTY1 + 8 * NSLOT;
constexpr uint32_t B_FULL2  = B_KV + 64;
constexpr uint32_t B_OE     = B_FULL2 + 24;
constexpr uint32_t B_WO     = B_OE + 16;
constexpr uint32_t B_O      = B_WO + 8;
constexpr uint32_t B_EMPTY2 = B_O + 32;
constexpr uint32_t B_OEE    = B_EMPTY2 + 24;
constexpr uint32_t B_ADONE  = B_OEE + 16;
constexpr uint32_t SM_TOTAL = B_ADONE + 8;

__device__ __align__(1024) uint8_t gQ[32 * SEQ * 32];
__device__ __align__(1024) uint8_t gKV[32 * 16 * 8192];
__device__ __align__(1024) uint8_t gH[32 * 28 * 8192];
__device__ __align__(1024) uint8_t gO[32 * 8 * 8192];
__device__ uint32_t gFlag[72 * 32];
constexpr int F_QKV = 0, F_H = 8, F_O = 40;
#define TSTAMP(role, i)

template<int TB, int SD> __device__ __forceinline__ void wg_rs_n24(float* d, const uint32_t* a, uint64_t db) {
  if (SD)
    asm volatile("wgmma.mma_async.sync.aligned.m64n24k16.f32.bf16.bf16 {%0,%1,%2,%3,%4,%5,%6,%7,%8,%9,%10,%11}, {%12,%13,%14,%15}, %16, 1, 1, 1, %17;"
      : "+f"(d[0]),"+f"(d[1]),"+f"(d[2]),"+f"(d[3]),"+f"(d[4]),"+f"(d[5]),"+f"(d[6]),"+f"(d[7]),"+f"(d[8]),"+f"(d[9]),"+f"(d[10]),"+f"(d[11])
      : "r"(a[0]), "r"(a[1]), "r"(a[2]), "r"(a[3]), "l"(db), "n"(TB));
  else
    asm volatile("wgmma.mma_async.sync.aligned.m64n24k16.f32.bf16.bf16 {%0,%1,%2,%3,%4,%5,%6,%7,%8,%9,%10,%11}, {%12,%13,%14,%15}, %16, 0, 1, 1, %17;"
      : "=f"(d[0]),"=f"(d[1]),"=f"(d[2]),"=f"(d[3]),"=f"(d[4]),"=f"(d[5]),"=f"(d[6]),"=f"(d[7]),"=f"(d[8]),"=f"(d[9]),"=f"(d[10]),"=f"(d[11])
      : "r"(a[0]), "r"(a[1]), "r"(a[2]), "r"(a[3]), "l"(db), "n"(TB));
}
template<int TB, int SD> __device__ __forceinline__ void wg_rs_n64(float* d, const uint32_t* a, uint64_t db) {
  if (SD)
    asm volatile("wgmma.mma_async.sync.aligned.m64n64k16.f32.bf16.bf16 {%0,%1,%2,%3,%4,%5,%6,%7,%8,%9,%10,%11,%12,%13,%14,%15,%16,%17,%18,%19,%20,%21,%22,%23,%24,%25,%26,%27,%28,%29,%30,%31}, {%32,%33,%34,%35}, %36, 1, 1, 1, %37;"
      : "+f"(d[0]),"+f"(d[1]),"+f"(d[2]),"+f"(d[3]),"+f"(d[4]),"+f"(d[5]),"+f"(d[6]),"+f"(d[7]),"+f"(d[8]),"+f"(d[9]),"+f"(d[10]),"+f"(d[11]),"+f"(d[12]),"+f"(d[13]),"+f"(d[14]),"+f"(d[15]),"+f"(d[16]),"+f"(d[17]),"+f"(d[18]),"+f"(d[19]),"+f"(d[20]),"+f"(d[21]),"+f"(d[22]),"+f"(d[23]),"+f"(d[24]),"+f"(d[25]),"+f"(d[26]),"+f"(d[27]),"+f"(d[28]),"+f"(d[29]),"+f"(d[30]),"+f"(d[31])
      : "r"(a[0]), "r"(a[1]), "r"(a[2]), "r"(a[3]), "l"(db), "n"(TB));
  else
    asm volatile("wgmma.mma_async.sync.aligned.m64n64k16.f32.bf16.bf16 {%0,%1,%2,%3,%4,%5,%6,%7,%8,%9,%10,%11,%12,%13,%14,%15,%16,%17,%18,%19,%20,%21,%22,%23,%24,%25,%26,%27,%28,%29,%30,%31}, {%32,%33,%34,%35}, %36, 0, 1, 1, %37;"
      : "=f"(d[0]),"=f"(d[1]),"=f"(d[2]),"=f"(d[3]),"=f"(d[4]),"=f"(d[5]),"=f"(d[6]),"=f"(d[7]),"=f"(d[8]),"=f"(d[9]),"=f"(d[10]),"=f"(d[11]),"=f"(d[12]),"=f"(d[13]),"=f"(d[14]),"=f"(d[15]),"=f"(d[16]),"=f"(d[17]),"=f"(d[18]),"=f"(d[19]),"=f"(d[20]),"=f"(d[21]),"=f"(d[22]),"=f"(d[23]),"=f"(d[24]),"=f"(d[25]),"=f"(d[26]),"=f"(d[27]),"=f"(d[28]),"=f"(d[29]),"=f"(d[30]),"=f"(d[31])
      : "r"(a[0]), "r"(a[1]), "r"(a[2]), "r"(a[3]), "l"(db), "n"(TB));
}
template<int TB> __device__ __forceinline__ void wg_ss_n64(float* d, uint64_t da, uint64_t db) {
  asm volatile("wgmma.mma_async.sync.aligned.m64n64k16.f32.bf16.bf16 {%0,%1,%2,%3,%4,%5,%6,%7,%8,%9,%10,%11,%12,%13,%14,%15,%16,%17,%18,%19,%20,%21,%22,%23,%24,%25,%26,%27,%28,%29,%30,%31}, %32, %33, 1, 1, 1, 0, %34;"
    : "+f"(d[0]),"+f"(d[1]),"+f"(d[2]),"+f"(d[3]),"+f"(d[4]),"+f"(d[5]),"+f"(d[6]),"+f"(d[7]),"+f"(d[8]),"+f"(d[9]),"+f"(d[10]),"+f"(d[11]),"+f"(d[12]),"+f"(d[13]),"+f"(d[14]),"+f"(d[15]),"+f"(d[16]),"+f"(d[17]),"+f"(d[18]),"+f"(d[19]),"+f"(d[20]),"+f"(d[21]),"+f"(d[22]),"+f"(d[23]),"+f"(d[24]),"+f"(d[25]),"+f"(d[26]),"+f"(d[27]),"+f"(d[28]),"+f"(d[29]),"+f"(d[30]),"+f"(d[31])
    : "l"(da), "l"(db), "n"(TB));
}
template<int TB> __device__ __forceinline__ void wg_ss_n128(float* d, uint64_t da, uint64_t db) {
  asm volatile("wgmma.mma_async.sync.aligned.m64n128k16.f32.bf16.bf16 {%0,%1,%2,%3,%4,%5,%6,%7,%8,%9,%10,%11,%12,%13,%14,%15,%16,%17,%18,%19,%20,%21,%22,%23,%24,%25,%26,%27,%28,%29,%30,%31,%32,%33,%34,%35,%36,%37,%38,%39,%40,%41,%42,%43,%44,%45,%46,%47,%48,%49,%50,%51,%52,%53,%54,%55,%56,%57,%58,%59,%60,%61,%62,%63}, %64, %65, 1, 1, 1, 0, %66;"
    : "+f"(d[0]),"+f"(d[1]),"+f"(d[2]),"+f"(d[3]),"+f"(d[4]),"+f"(d[5]),"+f"(d[6]),"+f"(d[7]),"+f"(d[8]),"+f"(d[9]),"+f"(d[10]),"+f"(d[11]),"+f"(d[12]),"+f"(d[13]),"+f"(d[14]),"+f"(d[15]),"+f"(d[16]),"+f"(d[17]),"+f"(d[18]),"+f"(d[19]),"+f"(d[20]),"+f"(d[21]),"+f"(d[22]),"+f"(d[23]),"+f"(d[24]),"+f"(d[25]),"+f"(d[26]),"+f"(d[27]),"+f"(d[28]),"+f"(d[29]),"+f"(d[30]),"+f"(d[31]),"+f"(d[32]),"+f"(d[33]),"+f"(d[34]),"+f"(d[35]),"+f"(d[36]),"+f"(d[37]),"+f"(d[38]),"+f"(d[39]),"+f"(d[40]),"+f"(d[41]),"+f"(d[42]),"+f"(d[43]),"+f"(d[44]),"+f"(d[45]),"+f"(d[46]),"+f"(d[47]),"+f"(d[48]),"+f"(d[49]),"+f"(d[50]),"+f"(d[51]),"+f"(d[52]),"+f"(d[53]),"+f"(d[54]),"+f"(d[55]),"+f"(d[56]),"+f"(d[57]),"+f"(d[58]),"+f"(d[59]),"+f"(d[60]),"+f"(d[61]),"+f"(d[62]),"+f"(d[63])
    : "l"(da), "l"(db), "n"(TB));
}

__device__ __forceinline__ void wg_fence() { asm volatile("wgmma.fence.sync.aligned;" ::: "memory"); }
__device__ __forceinline__ void wg_commit() { asm volatile("wgmma.commit_group.sync.aligned;" ::: "memory"); }
template <int N> __device__ __forceinline__ void wg_wait() { asm volatile("wgmma.wait_group.sync.aligned %0;" ::"n"(N) : "memory"); }
template <int N> __device__ __forceinline__ void pin(float* r) {
#pragma unroll
  for (int i = 0; i < N; i++) asm volatile("" : "+f"(r[i])::"memory");
}
template <int N> __device__ __forceinline__ void clear(float* r) {
#pragma unroll
  for (int i = 0; i < N; i++) r[i] = 0.f;
  pin<N>(r);
}
template <int N> __device__ __forceinline__ void pin(uint32_t* r) {
#pragma unroll
  for (int i = 0; i < N; i++) asm volatile("" : "+r"(r[i])::"memory");
}
__device__ __forceinline__ uint64_t mkdesc(uint32_t addr, uint32_t lbo, uint32_t sbo, uint32_t swz) {
  return (uint64_t)((addr & 0x3FFFF) >> 4) | ((uint64_t)(lbo >> 4) << 16) | ((uint64_t)(sbo >> 4) << 32) | ((uint64_t)swz << 62);
}
__device__ __forceinline__ void mbar_init(uint32_t b, int c) { asm volatile("mbarrier.init.shared::cta.b64 [%0], %1;" ::"r"(b), "r"(c) : "memory"); }
__device__ __forceinline__ void mbar_expect(uint32_t b, int n) { asm volatile("mbarrier.arrive.expect_tx.shared::cta.b64 _, [%0], %1;" ::"r"(b), "r"(n) : "memory"); }
__device__ __forceinline__ void mbar_arrive(uint32_t b) { asm volatile("mbarrier.arrive.shared::cta.b64 _, [%0];" ::"r"(b) : "memory"); }
__device__ __forceinline__ bool mbar_try(uint32_t b, uint32_t ph) {
  uint32_t ok;
  asm volatile("{.reg .pred p; mbarrier.try_wait.parity.shared::cta.b64 p, [%1], %2; selp.u32 %0, 1, 0, p;}" : "=r"(ok) : "r"(b), "r"(ph) : "memory");
  return ok;
}
__device__ __forceinline__ void mbar_wait(uint32_t b, uint32_t ph) {
  if (mbar_try(b, ph)) return;
#pragma unroll 1
  for (int i = 0; i < (1 << 16); i++) {
    uint32_t ok;
    asm volatile("{.reg .pred p; mbarrier.try_wait.parity.shared::cta.b64 p, [%1], %2, 20000; selp.u32 %0, 1, 0, p;}" : "=r"(ok) : "r"(b), "r"(ph) : "memory");
    if (ok) return;
  }
  __trap();
}
__device__ __forceinline__ void bulk_load(uint32_t dst, const void* src, int bytes, uint32_t bar) {
  asm volatile("cp.async.bulk.shared::cluster.global.mbarrier::complete_tx::bytes [%0], [%1], %2, [%3];" ::"r"(dst), "l"(src), "r"(bytes), "r"(bar) : "memory");
}
__device__ __forceinline__ void tma_load(uint32_t dst, const CUtensorMap* m, int c0, int c1, uint32_t bar) {
  asm volatile("cp.async.bulk.tensor.2d.shared::cluster.global.mbarrier::complete_tx::bytes [%0], [%1, {%2, %3}], [%4];" ::"r"(dst), "l"(m), "r"(c0), "r"(c1), "r"(bar) : "memory");
}
__device__ __forceinline__ void tma_prefetch(const CUtensorMap* m, int c0, int c1) {
  asm volatile("cp.async.bulk.prefetch.tensor.2d.L2.global [%0, {%1, %2}];" ::"l"(m), "r"(c0), "r"(c1) : "memory");
}
__device__ __forceinline__ bool elect() {
  uint32_t r;
  asm volatile("{.reg .pred p; elect.sync _|p, 0xffffffff; selp.u32 %0, 1, 0, p;}" : "=r"(r));
  return r;
}
__device__ __forceinline__ void bar_sync(int id, int n) { asm volatile("bar.sync %0, %1;" ::"r"(id), "r"(n) : "memory"); }
__device__ __forceinline__ void bar_arrive(int id, int n) { asm volatile("bar.arrive %0, %1;" ::"r"(id), "r"(n) : "memory"); }
__device__ __forceinline__ bool bar_or(int id, int n, bool v) {
  uint32_t r;
  asm volatile("{.reg .pred p, q; setp.ne.u32 q, %3, 0; bar.red.or.pred p, %1, %2, q; selp.u32 %0, 1, 0, p;}" : "=r"(r) : "r"(id), "r"(n), "r"((uint32_t)v) : "memory");
  return r;
}
__device__ __forceinline__ void flag_add(int f) { asm volatile("red.release.gpu.global.add.u32 [%0], 1;" ::"l"(gFlag + f * 32) : "memory"); }
__device__ __forceinline__ void flag_wait(int f, uint32_t target, uint32_t ns) {
#pragma unroll 1
  for (int i = 0; i < (1 << 22); i++) {
    uint32_t v;
    asm volatile("ld.acquire.gpu.global.u32 %0, [%1];" : "=r"(v) : "l"(gFlag + f * 32) : "memory");
    if ((int)(v - target) >= 0) { asm volatile("fence.proxy.async.global;" ::: "memory"); return; }
    __nanosleep(ns);
  }
  __trap();
}
__device__ __forceinline__ float ex2(float x) { float y; asm("ex2.approx.ftz.f32 %0, %1;" : "=f"(y) : "f"(x)); return y; }
__device__ __forceinline__ float rcp(float x) { float y; asm("rcp.approx.ftz.f32 %0, %1;" : "=f"(y) : "f"(x)); return y; }
__device__ __forceinline__ uint32_t packbf(float lo, float hi) { uint32_t d; asm("cvt.rn.bf16x2.f32 %0, %1, %2;" : "=r"(d) : "f"(hi), "f"(lo)); return d; }
__device__ __forceinline__ float bfr(float x) { return __bfloat162float(__float2bfloat16(x)); }
__device__ __forceinline__ uint32_t hmul(uint32_t a, uint32_t b) { uint32_t d; asm("mul.rn.bf16x2 %0, %1, %2;" : "=r"(d) : "r"(a), "r"(b)); return d; }
__device__ __forceinline__ uint32_t hadd(uint32_t a, uint32_t b) { uint32_t d; asm("add.rn.bf16x2 %0, %1, %2;" : "=r"(d) : "r"(a), "r"(b)); return d; }
__device__ __forceinline__ uint32_t hsub(uint32_t a, uint32_t b) { uint32_t d; asm("sub.rn.bf16x2 %0, %1, %2;" : "=r"(d) : "r"(a), "r"(b)); return d; }
__device__ __forceinline__ void hmma(float* c, const uint4& a, uint32_t b0, uint32_t b1) {
  asm("mma.sync.aligned.m16n8k16.row.col.f32.bf16.bf16.f32 {%0,%1,%2,%3},{%4,%5,%6,%7},{%8,%9},{%0,%1,%2,%3};"
      : "+f"(c[0]), "+f"(c[1]), "+f"(c[2]), "+f"(c[3]) : "r"(a.x), "r"(a.y), "r"(a.z), "r"(a.w), "r"(b0), "r"(b1));
}
constexpr float LOG2E = 1.4426950408889634f;

__device__ __forceinline__ uint32_t exp_poly(float lo, float hi, uint32_t half2) {
  uint32_t u, mh, p;
  asm("cvt.pack.sat.s16.s32 %0, %1, %2;" : "=r"(u) : "r"(__float_as_uint(hi)), "r"(__float_as_uint(lo)));
  asm("lop3.b32 %0, %1, 0x007F007F, %2, 0xEA;" : "=r"(mh) : "r"(u), "r"(half2));
  asm("fma.rn.bf16x2 %0, %1, %2, %3;" : "=r"(p) : "r"(u), "r"(mh), "r"(u & 0xFF80FF80u));
  return p;
}
__device__ __forceinline__ void softmax64(float* s, uint32_t* p, uint32_t half2) {
  pin<32>(s);
#pragma unroll
  for (int j = 0; j < 8; j++) {
#pragma unroll
    for (int r = 0; r < 2; r++) {
      const float a = s[4 * j + 2 * r], b = s[4 * j + 2 * r + 1];
      p[2 * j + r] = ((POLYMASK >> j) & 1) ? exp_poly(a, b, half2) : packbf(ex2(a), ex2(b));
    }
  }
  pin<16>(p);
}

struct Tile { int kind, c0, c1; };
__device__ __forceinline__ Tile tile_of(int cg, int t) {
  const int c2 = cg >> 1;
  Tile r;
  if (cg & 1) {
    if (t == 0) { r.kind = 1; r.c0 = c2 * 128; r.c1 = r.c0 + 64; }
    else { r.kind = 2; r.c0 = r.c1 = (7 * c2 + 2 + t) * 64; }
  } else {
    if (t < 2) { r.kind = 0; r.c0 = 512 + c2 * 128 + t * 64; r.c1 = r.c0 + 512; }
    else { r.kind = 2; r.c0 = r.c1 = (7 * c2 + t - 2) * 64; }
  }
  return r;
}

__global__ void __launch_bounds__(NTHREADS, 1)
fused_kernel(const __grid_constant__ CUtensorMap mQKV, const __grid_constant__ CUtensorMap mW1, const __grid_constant__ CUtensorMap mW3,
             const __grid_constant__ CUtensorMap mW2, const __grid_constant__ CUtensorMap mWO, const bf16* __restrict__ x, bf16* __restrict__ out,
             uint32_t zero) {
  extern __shared__ __align__(1024) uint8_t smem[];
  const uint32_t sb = (uint32_t)__cvta_generic_to_shared(smem);
  const int tid = threadIdx.x, lane = tid & 31, g = lane >> 2, t = lane & 3;
  const int warp = __shfl_sync(~0u, tid >> 5, 0), wg = warp >> 2, w = warp & 3;
  const int b = blockIdx.x;
  const int rb = b >> 3, cg = b & 7;
  const int head = b & 31, qb = b >> 5;
  const int rEarly = (rb >> 2) * 8 + ((0x3052 >> ((rb & 3) * 4)) & 7), rLate = (rb >> 2) * 8 + ((0x6741 >> ((rb & 3) * 4)) & 7);

  if (wg == 4) {
    asm volatile("setmaxnreg.dec.sync.aligned.u32 32;");
    if (w == 0) {
      uint32_t epoch;
      asm volatile("ld.relaxed.gpu.global.u32 %0, [%1];" : "=r"(epoch) : "l"(gFlag + F_O * 32) : "memory");
      if (lane < 2 * NSLOT) mbar_init(sb + B_FULL1 + 8 * lane, 1);
      if (lane < NSLOT) mbar_init(sb + B_EMPTY1 + 8 * lane, 8);
      if (lane < 24) mbar_init(sb + B_KV + 8 * lane, lane < 18 ? 1 : lane < 23 ? 4 : 12);
      asm volatile("fence.mbarrier_init.release.cluster;" ::: "memory");
      asm volatile("fence.proxy.async.shared::cta;" ::: "memory");
      __syncwarp();
      bar_arrive(1, 544);
      epoch = (epoch >> 5) + 1;
      int slot = 0;
      uint32_t ph = 1;
#pragma unroll 1
      for (int tI = 0; tI < 5; tI++) {
        const Tile tl = tile_of(cg, tI);
        const CUtensorMap *m0 = tl.kind == 2 ? &mW1 : &mQKV, *m1 = tl.kind == 2 ? &mW3 : &mQKV;
#pragma unroll 1
        for (int k = 0; k < 8; k++) {
          const uint32_t full = sb + B_FULL1 + 8 * ((tI & 1) * NSLOT + slot), dst = sb + SM_RING + slot * 16384;
          if (tI == 0 && k == 2) bar_sync(2, 544);
          if (tI == 4 && k == 0) flag_wait(F_QKV + (head >> 2), epoch * 32, 32);
          if (tI == 0 && k == NSLOT) {
            const int i = 2 * NSLOT + rb + lane * 16;
            if (i < 80) {
              const Tile tp = tile_of(cg, i >> 4);
              tma_prefetch((i & 1) ? (tp.kind == 2 ? &mW3 : &mQKV) : (tp.kind == 2 ? &mW1 : &mQKV), (i & 1) ? tp.c1 : tp.c0, ((i >> 1) & 7) * 64);
            }
            __syncwarp();
          }
          mbar_wait(sb + B_EMPTY1 + 8 * slot, ph);
          if (elect()) {
            mbar_expect(full, 16384);
            tma_load(dst, m0, tl.c0, k * 64, full);
            tma_load(dst + 8192, m1, tl.c1, k * 64, full);
          }
          if (++slot == NSLOT) { slot = 0; ph ^= 1; }
        }
      }
#pragma unroll 1
      for (int j = 0; j < 8; j++) {
        if (j >= 8 - NSLOT) {
          mbar_wait(sb + B_EMPTY1 + 8 * slot, ph);
          if (++slot == NSLOT) { slot = 0; ph ^= 1; }
        }
        if (elect()) {
          mbar_expect(sb + B_KV + 8 * j, 16384);
          bulk_load(sb + SM_A + j * 16384, gKV + (size_t)head * 131072 + j * 16384, 16384, sb + B_KV + 8 * j);
        }
      }
      flag_wait(F_H + rEarly, epoch * 28, 100);
      flag_wait(F_H + rLate, epoch * 28, 100);
      slot = 0; ph = 1;
#pragma unroll 1
      for (int n = 0; n < 31; n++) {
        const uint32_t full = sb + B_FULL2 + 8 * slot, dst = sb + SM_RING + slot * 24576;
        mbar_wait(sb + B_EMPTY2 + 8 * slot, ph);
        if (n < 28 && elect()) {
          mbar_expect(full, 24576);
          tma_load(dst, &mW2, cg * 64, n * 64, full);
          bulk_load(dst + 8192, gH + (size_t)(rEarly * 28 + n) * 8192, 8192, full);
          bulk_load(dst + 16384, gH + (size_t)(rLate * 28 + n) * 8192, 8192, full);
        }
        if (++slot == 3) { slot = 0; ph ^= 1; }
      }
      if (elect()) {
        mbar_expect(sb + B_WO, 65536);
#pragma unroll 1
        for (int k = 0; k < 8; k++) tma_load(sb + SM_RING + k * 8192, &mWO, cg * 64, k * 64, sb + B_WO);
      }
      flag_wait(F_O + rEarly, epoch * 32, 200);
#pragma unroll 1
      for (int n = 0; n < 8; n++) {
        mbar_wait(sb + B_OEE + 8 * (n & 1), ((n >> 1) & 1) ^ 1);
        if (elect()) {
          mbar_expect(sb + B_OE + 8 * (n & 1), 8192);
          bulk_load(sb + SM_RING + 65536 + (n & 1) * 8192, gO + (size_t)(rEarly * 8 + n) * 8192, 8192, sb + B_OE + 8 * (n & 1));
        }
      }
      mbar_wait(sb + B_ADONE, 0);
      flag_wait(F_O + rLate, epoch * 32, 20);
      if (elect()) {
#pragma unroll
        for (int i = 0; i < 4; i++) {
          mbar_expect(sb + B_O + 8 * i, 16384);
          bulk_load(sb + SM_A + i * 16384, gO + (size_t)rLate * 65536 + i * 16384, 16384, sb + B_O + 8 * i);
        }
      }
    } else {
      if (w < 3) {
#pragma unroll 1
        for (int tI = w - 1; tI < 5; tI += 2) {
          const Tile tl = tile_of(cg, tI);
          bar_sync(3 + w, 288);
          if (lane < (tl.kind ? 2 : 1)) flag_add(tl.kind == 2 ? F_H + rb * 2 + lane : F_QKV + ((tl.c0 >> 6) & 7) + lane);
          __syncwarp();
        }
      }
#pragma unroll 1
      for (int i = 0; i < (w == 2 ? 2 : 3); i++) {
        bar_sync(12 + w, 160);
        if (lane == 0) flag_add(F_O + qb * 8 + (((w == 1 ? 0x102 : w == 2 ? 0x43 : 0x765) >> (i * 4)) & 7));
        __syncwarp();
      }
    }
    return;
  }

  TSTAMP(wg, 0);
  uint4 xv[16];
  {
    const uint4* xp = (const uint4*)(x + (size_t)(rb * 128 + warp * 8 + g) * DM);
#pragma unroll
    for (int j = 0; j < 16; j++) xv[j] = __ldg(xp + 4 * (j ^ (g & 1)) + t);
  }
  asm volatile("setmaxnreg.inc.sync.aligned.u32 112;");

  {
    if (tid < 128) ((uint32_t*)(smem + SM_ONES))[tid] = 0x3F803F80u;
    {
      const int n = tid >> 3, k = (tid & 7) * 2;
      const bool poly = (POLYMASK >> (n >> 3)) & 1;
      const float cm = -127.f + 0.5849625f - 0.0020f, chi = bfr(cm), clo = cm - chi, sc = poly ? 0x1p-71f : 0x1p71f;
      float v0 = 0.f, v1 = 0.f;
      if (k == 0) { v0 = sc; v1 = sc; }
      if (k == 2) { v0 = sc; v1 = poly ? 0.f : chi * sc; }
      if (k == 4) { v0 = poly ? 0.f : clo * sc; }
      *(uint32_t*)(smem + SM_BIAS + n * 32 + (((k >> 3) ^ ((n >> 2) & 1)) << 4) + (k & 7) * 2) = packbf(v0, v1);
    }
    float cs[4] = {0.f, 0.f, 0.f, 0.f}, ca[4] = {0.f, 0.f, 0.f, 0.f}, cb[4] = {0.f, 0.f, 0.f, 0.f};
#pragma unroll
    for (int j = 0; j < 16; j++) {
      hmma(cs, xv[j], 0x3F803F80u, 0x3F803F80u);
      hmma(ca, xv[j], xv[j].x, xv[j].z);
      hmma(cb, xv[j], xv[j].y, xv[j].w);
    }
    bar_arrive(2, 544);
    const float mean = (cs[0] + cs[2]) * (1.f / DM);
    const uint32_t m2 = packbf(mean, mean);
    if (m2 != 0x12345678) TSTAMP(4, wg);
    const int row = warp * 8 + g;
    if (t == (g >> 1)) {
      const float var = fmaxf(((g & 1) ? ca[1] + cb[3] : ca[0] + cb[2]) * (1.f / DM) - mean * mean, 0.f);
      ((float*)(smem + SM_RSTD))[row] = 1.f / bfr(sqrtf(bfr(bfr(var) + 1e-5f)));
    }
#pragma unroll
    for (int j = 0; j < 16; j++) {
      const int c = 4 * (j ^ (g & 1)) + t;
      uint4 d;
      d.x = hsub(xv[j].x, m2); d.y = hsub(xv[j].y, m2); d.z = hsub(xv[j].z, m2); d.w = hsub(xv[j].w, m2);
      *(uint4*)(smem + SM_A + (c >> 3) * 16384 + row * 128 + (((c & 7) ^ g) << 4)) = d;
    }
    TSTAMP(4, 4 + wg);
    asm volatile("fence.proxy.async.shared::cta;" ::: "memory");
    bar_sync(1, 544);
  }
  TSTAMP(wg, 1);
  const int pair = wg >> 1, half = wg & 1;

  {
    uint32_t par = 0;
    const uint64_t dA0 = mkdesc(sb + SM_A + half * 8192, 16, 1024, 1), dB0 = mkdesc(sb + SM_RING, 8192, 1024, 1);
#pragma unroll 1
    for (int tI = pair; tI < 5; tI += 2) {
      float acc[64];
      clear<64>(acc);
      int slot = (tI * 8) % NSLOT, prev = 0;
#pragma unroll 1
      for (int k = 0; k < 8; k++) {
        mbar_wait(sb + B_FULL1 + 8 * (pair * NSLOT + slot), (par >> slot) & 1);
        par ^= 1u << slot;
        const uint64_t dA = dA0 + k * 1024, dB = dB0 + slot * 1024;
        wg_fence();
        wg_ss_n128<1>(acc, dA, dB);
        wg_ss_n128<1>(acc, dA + 2, dB + 128);
        wg_ss_n128<1>(acc, dA + 4, dB + 256);
        wg_ss_n128<1>(acc, dA + 6, dB + 384);
        wg_commit();
        if (k > 0) {
          wg_wait<1>();
          if (lane == 0) mbar_arrive(sb + B_EMPTY1 + 8 * prev);
        }
        prev = slot;
        if (++slot == NSLOT) slot = 0;
      }
      wg_wait<0>();
      if (lane == 0) mbar_arrive(sb + B_EMPTY1 + 8 * prev);
      pin<64>(acc);
      TSTAMP(wg, 2 + (tI >> 1) * 2);
      const Tile tl = tile_of(cg, tI);
      const int lrow = half * 64 + w * 16 + g;
      const float r0 = ((const float*)(smem + SM_RSTD))[lrow], r1 = ((const float*)(smem + SM_RSTD))[lrow + 8];
      if (tl.kind == 2) {
        uint32_t* hp = (uint32_t*)(gH + (size_t)((rb * 2 + half) * 28 + (tl.c0 >> 6)) * 8192 + w * 256) + lane;
#pragma unroll
        for (int j = 0; j < 8; j++) {
#pragma unroll
          for (int r = 0; r < 2; r++) {
            const float rs = r ? r1 : r0, e = -LOG2E * rs, q = rs * rs;
            const float g0 = acc[4 * j + 2 * r], g1 = acc[4 * j + 2 * r + 1];
            const float h0 = (g0 * q) * acc[32 + 4 * j + 2 * r] * rcp(1.f + ex2(g0 * e));
            const float h1 = (g1 * q) * acc[33 + 4 * j + 2 * r] * rcp(1.f + ex2(g1 * e));
            hp[j * 256 + r * 32] = packbf(h0, h1);
          }
        }
      } else {
        const int hg = (tl.c0 >> 6) & 7;
#pragma unroll
        for (int u = 0; u < 2; u++) {
#pragma unroll
          for (int r = 0; r < 2; r++) {
            float sc = r ? r1 : r0;
            uint8_t* p;
            size_t hs;
            if (tl.kind == 1) {
              sc *= 0.25f * LOG2E * 0x1p-71f;
              p = gQ + (size_t)(hg + u) * 4 * 65536 + (size_t)(rb * 128 + lrow + r * 8) * 32 + t * 8;
              hs = 65536;
            } else {
              if (u == 0) sc *= ((POLYMASK >> (2 * w + r)) & 1) ? 0x1p-71f : 0x1p71f;
              p = gKV + (size_t)hg * 4 * 131072 + rb * 8192 + u * 4096 + (lrow + r * 8) * 32 + ((t * 8) ^ ((g & 4) << 2));
              hs = 131072;
            }
#pragma unroll
            for (int hh = 0; hh < 4; hh++) {
              const float* a = acc + u * 32 + hh * 8 + 2 * r;
              *(uint2*)(p + hh * hs) = make_uint2(packbf(a[0] * sc, a[1] * sc), packbf(a[4] * sc, a[5] * sc));
            }
          }
        }
      }
      bar_arrive(4 + pair, 288);
      TSTAMP(wg, 3 + (tI >> 1) * 2);
    }
  }

  if (wg < 3) {
    constexpr uint64_t VS = (uint64_t)(32 - (32LL << 16));
    const uint32_t half2 = 0x3F003F00u + zero;
    const uint64_t dBias = mkdesc(sb + SM_BIAS, 16, 256, 3);
    const int nseg = wg == 1 ? 4 : 3;
    const uint32_t segs = wg == 0 ? 0x102 : wg == 1 ? 0x4352 : 0x765;
    int ready = wg == 0 ? 2 : 0;
    mbar_wait(sb + B_KV + 8 * ready, 0);
    const uint8_t* qbase = gQ + (size_t)head * 65536 + (size_t)(qb * 512 + w * 16) * 32;
    if (lane < 4 * nseg) asm volatile("prefetch.global.L1 [%0];" ::"l"(qbase + ((segs >> (lane & ~3)) & 7) * 2048 + (lane & 3) * 128));
    TSTAMP(wg, 8);
    bool exact = false;
#pragma unroll 1
    for (int seg = 0; seg < nseg; seg++) {
      int c0 = 0, c1 = 16, mode = 0;
      if (wg == 1) { if (seg < 2) { c0 = seg * 11; c1 = c0 + 5; mode = 1; } }
      else if (seg == 0) { c0 = wg ? 0 : 5; c1 = c0 + 11; mode = 2; }
      const int rbl = (segs >> (seg * 4)) & 7, rblk = qb * 8 + rbl;
      if ((seg > 0 || exact) && ready < 8) {
#pragma unroll 1
        for (int j = 0; j < 8; j++) mbar_wait(sb + B_KV + 8 * j, 0);
        ready = 8;
      }
      uint32_t q[4], qa[4];
      {
        const uint32_t* qp = (const uint32_t*)(qbase + rbl * 2048 + g * 32) + t;
        q[0] = __ldca(qp); q[1] = __ldca(qp + 64); q[2] = __ldca(qp + 4); q[3] = __ldca(qp + 68);
      }
      if (seg == nseg - 1 && q[0] != 0x12345678) TSTAMP(wg, 13);
      const uint32_t va = sb + SM_A + 4096 + c0 * 8192;
      const uint64_t dV0 = mkdesc(va, sb + SM_ONES - va, 256, 3);
      float o[12], bias[2];
      {
        const int nmax = exact ? (c1 - c0) * 2 : 1;
        float s[32];
        uint32_t p0[16], p1[16];
        float mp0 = -INFINITY, mp1 = -INFINITY, mm0 = -INFINITY, mm1 = -INFINITY;
#pragma unroll 1
        for (int i = 0; i < nmax; i++) {
          wg_fence();
          wg_rs_n64<0, 0>(s, q, dV0 - 256 + (i >> 1) * 512 + (i & 1) * 128);
          wg_commit();
          wg_wait<0>();
          pin<32>(s);
#pragma unroll
          for (int j = 0; j < 8; j++) {
            if ((POLYMASK >> j) & 1) { mp0 = fmaxf(mp0, fmaxf(s[4 * j], s[4 * j + 1])); mp1 = fmaxf(mp1, fmaxf(s[4 * j + 2], s[4 * j + 3])); }
            else { mm0 = fmaxf(mm0, fmaxf(s[4 * j], s[4 * j + 1])); mm1 = fmaxf(mm1, fmaxf(s[4 * j + 2], s[4 * j + 3])); }
          }
        }
#pragma unroll
        for (int r = 0; r < 2; r++) {
          float v = fmaxf(r ? mm1 : mm0, ((r ? mp1 : mp0) * 0x1p71f) * 0x1p71f);
          v = fmaxf(v, __shfl_xor_sync(~0u, v, 1));
          v = fmaxf(v, __shfl_xor_sync(~0u, v, 2));
          bias[r] = rintf(64.f - v);
          const float y = bias[r] * 0x1p-71f, hi = bfr(y), mid = bfr(y - hi);
          qa[r] = t == 0 ? packbf(hi, mid) : t == 1 ? packbf(y - hi - mid, 0x1p-71f) : t == 2 ? 0x00001C00u : 0u;
          qa[2 + r] = qa[r] & zero;
        }
        if (seg == nseg - 1 && qa[0] != 0x12345678) TSTAMP(wg, 14);
        clear<12>(o);
        uint64_t c = dV0;
        wg_fence();
        wg_rs_n64<0, 0>(s, qa, dBias);
        wg_rs_n64<0, 1>(s, q, c - 256);
        wg_commit();
        wg_wait<0>();
        if (seg == nseg - 1) TSTAMP(wg, 15);
#pragma unroll 1
        for (int ci = c0; ci < c1;) {
        if (ready < 7) mbar_wait(sb + B_KV + 8 * ++ready, 0);
        ci = ready >= 7 ? c1 : min(c1, 2 * ready);
        const uint32_t cend = (uint32_t)(dV0 + (uint64_t)(ci - c0) * 16 * VS);
#pragma unroll 1
        do {
          softmax64(s, p0, half2);
          wg_fence();
          wg_rs_n64<0, 0>(s, qa, dBias);
          wg_rs_n64<0, 1>(s, q, c - 128);
          wg_commit();
#pragma unroll
          for (int k = 0; k < 4; k++) wg_rs_n24<1, 1>(o, p0 + 4 * k, c + k * VS);
          wg_commit();
          wg_wait<1>();
          softmax64(s, p1, half2);
          wg_fence();
          wg_rs_n64<0, 0>(s, qa, dBias);
          wg_rs_n64<0, 1>(s, q, c + 256);
          wg_commit();
#pragma unroll
          for (int k = 0; k < 4; k++) wg_rs_n24<1, 1>(o, p1 + 4 * k, c + (4 + k) * VS);
          wg_commit();
          c += 16 * VS;
          wg_wait<1>();
        } while ((uint32_t)c != cend);
        }
        wg_wait<0>();
        pin<12>(o);
      }
      exact = __all_sync(~0u, bar_or(10 + wg, 128, !exact && !(o[8] < 0x1p90f && o[10] < 0x1p90f)));
      if (exact) { seg--; continue; }
      if (mode == 1) {
        float* mp = (float*)(smem + SM_MERGE + seg * 6144) + (tid & 127);
        o[9] = bias[0]; o[11] = bias[1];
#pragma unroll
        for (int i = 0; i < 12; i++) mp[i * 128] = o[i];
        bar_arrive(8 + seg, 256);
        continue;
      }
      if (mode == 2) {
        const float* mp = (const float*)(smem + SM_MERGE + (wg >> 1) * 6144) + (tid & 127);
        bar_sync(8 + (wg >> 1), 256);
#pragma unroll
        for (int r = 0; r < 2; r++) {
          const float bo = mp[(9 + 2 * r) * 128], bm = fminf(bo, bias[r]);
          const float fa = ex2(0.5f * (bm - bias[r])), fb = ex2(0.5f * (bm - bo));
          o[2 * r] = o[2 * r] * fa * fa + mp[(2 * r) * 128] * fb * fb;
          o[2 * r + 1] = o[2 * r + 1] * fa * fa + mp[(2 * r + 1) * 128] * fb * fb;
          o[4 + 2 * r] = o[4 + 2 * r] * fa * fa + mp[(4 + 2 * r) * 128] * fb * fb;
          o[5 + 2 * r] = o[5 + 2 * r] * fa * fa + mp[(5 + 2 * r) * 128] * fb * fb;
          o[8 + 2 * r] = o[8 + 2 * r] * fa * fa + mp[(8 + 2 * r) * 128] * fb * fb;
        }
      }
      if (seg == nseg - 1 && lane == 0) mbar_arrive(sb + B_ADONE);
#pragma unroll
      for (int r = 0; r < 2; r++) {
        const float inv = rcp(o[8 + 2 * r]);
        const uint32_t a = packbf(o[2 * r] * inv, o[2 * r + 1] * inv), c = packbf(o[4 + 2 * r] * inv, o[5 + 2 * r] * inv);
        const uint32_t e = __shfl_xor_sync(~0u, (t & 2) ? a : c, 2);
        *(uint2*)(gO + (size_t)(rblk * 8 + (head >> 2)) * 8192 + ((head & 3) * 2 + (t & 1)) * 1024 + (2 * w + r) * 128 + g * 16 + (t & 2) * 4) =
            (t & 2) ? make_uint2(e, c) : make_uint2(a, e);
      }
      bar_arrive(13 + wg, 160);
      TSTAMP(wg, 9 + seg);
    }
  } else {
    uint32_t gate[32];
    const uint64_t dB0 = mkdesc(sb + SM_RING, 8192, 1024, 1);
    {
      const uint64_t dA0 = mkdesc(sb + SM_RING + 8192, 1024, 128, 0);
      float acc[64];
      clear<64>(acc);
      int slot = 0;
      uint32_t ph = 0;
#pragma unroll 1
      for (int n = 0; n < 28; n++) {
        mbar_wait(sb + B_FULL2 + 8 * slot, ph);
        const uint64_t dA = dA0 + slot * 1536, dB = dB0 + slot * 1536;
        wg_fence();
#pragma unroll
        for (int k = 0; k < 4; k++) {
          wg_ss_n64<1>(acc, dA + k * 128, dB + k * 128);
          wg_ss_n64<1>(acc + 32, dA + 512 + k * 128, dB + k * 128);
        }
        wg_commit();
        wg_wait<0>();
        if (lane == 0) mbar_arrive(sb + B_EMPTY2 + 8 * slot);
        if (++slot == 3) { slot = 0; ph ^= 1; }
      }
      pin<64>(acc);
#pragma unroll
      for (int i = 0; i < 32; i++) {
        const float f0 = bfr(acc[2 * i]), f1 = bfr(acc[2 * i + 1]);
        gate[i] = packbf(f0 * rcp(1.f + ex2(-LOG2E * f0)), f1 * rcp(1.f + ex2(-LOG2E * f1)));
      }
    }
    TSTAMP(wg, 8);
#pragma unroll
    for (int pass = 0; pass < 2; pass++) {
      const size_t off = (size_t)((pass ? rLate : rEarly) * 64 + w * 16 + g) * DM + cg * 64 + (t & 1) * 8 + (t & 2) * 2;
      uint2 xr[8];
#pragma unroll
      for (int i = 0; i < 8; i++) xr[i] = __ldg((const uint2*)(x + off + (i & 1) * 8 * DM + (i >> 1) * 16));
      float acc[32];
      clear<32>(acc);
      if (pass == 0) {
        const uint64_t dA0 = mkdesc(sb + SM_RING + 65536, 1024, 128, 0);
        mbar_wait(sb + B_WO, 0);
#pragma unroll 1
        for (int n = 0; n < 8; n++) {
          mbar_wait(sb + B_OE + 8 * (n & 1), (n >> 1) & 1);
          wg_fence();
#pragma unroll
          for (int k = 0; k < 4; k++) wg_ss_n64<1>(acc, dA0 + (n & 1) * 512 + k * 128, dB0 + n * 512 + k * 128);
          wg_commit();
          wg_wait<0>();
          if (lane == 0) mbar_arrive(sb + B_OEE + 8 * (n & 1));
        }
      } else {
        mbar_wait(sb + B_ADONE, 0);
        const uint64_t dA = mkdesc(sb + SM_A, 1024, 128, 0);
#pragma unroll 1
        for (int n = 0; n < 4; n++) {
          mbar_wait(sb + B_O + 8 * n, 0);
          wg_fence();
#pragma unroll
          for (int k = 0; k < 8; k++) wg_ss_n64<1>(acc, dA + (n * 8 + k) * 128, dB0 + (n * 8 + k) * 128);
          wg_commit();
        }
        wg_wait<0>();
      }
      pin<32>(acc);
      TSTAMP(wg, 9 + 2 * pass);
#pragma unroll
      for (int i = 0; i < 8; i++) {
        const int ia = (i >> 1) * 4 + (i & 1), ib = ia + 2;
        const uint32_t ya = hmul(packbf(acc[2 * ia], acc[2 * ia + 1]), gate[pass * 16 + ia]);
        const uint32_t yb = hmul(packbf(acc[2 * ib], acc[2 * ib + 1]), gate[pass * 16 + ib]);
        const uint32_t e = __shfl_xor_sync(~0u, (t & 1) ? ya : yb, 1);
        const uint32_t lo = (t & 1) ? e : ya, hi = (t & 1) ? yb : e;
        *(uint2*)(out + off + (i & 1) * 8 * DM + (i >> 1) * 16) = make_uint2(hadd(xr[i].x, lo), hadd(xr[i].y, hi));
      }
      TSTAMP(wg, 10 + 2 * pass);
    }
  }
}

typedef CUresult (*EncodeFn)(CUtensorMap*, CUtensorMapDataType, cuuint32_t, void*, const cuuint64_t*, const cuuint64_t*, const cuuint32_t*,
                             const cuuint32_t*, CUtensorMapInterleave, CUtensorMapSwizzle, CUtensorMapL2promotion, CUtensorMapFloatOOBfill);

void make_map(EncodeFn enc, CUtensorMap* m, void* p, int rows, int cols) {
  const cuuint64_t dims[2] = {(cuuint64_t)cols, (cuuint64_t)rows}, strides[1] = {(cuuint64_t)cols * 2};
  const cuuint32_t box[2] = {64, 64}, es[2] = {1, 1};
  enc(m, CU_TENSOR_MAP_DATA_TYPE_BFLOAT16, 2, p, dims, strides, box, es, CU_TENSOR_MAP_INTERLEAVE_NONE, CU_TENSOR_MAP_SWIZZLE_128B,
      CU_TENSOR_MAP_L2_PROMOTION_L2_128B, CU_TENSOR_MAP_FLOAT_OOB_FILL_NONE);
}

}

extern "C" void kernel_launch(void* const* d_in, const int* in_sizes, int n_in, void* d_out, int out_size) {
  (void)in_sizes; (void)n_in; (void)out_size;
  void* fn = nullptr;
  cudaDriverEntryPointQueryResult qr;
  cudaGetDriverEntryPoint("cuTensorMapEncodeTiled", &fn, cudaEnableDefault, &qr);
  EncodeFn enc = (EncodeFn)fn;
  CUtensorMap mQKV, mW1, mW3, mW2, mWO;
  make_map(enc, &mQKV, d_in[1], DM, 3 * DM);
  make_map(enc, &mWO, d_in[2], DM, DM);
  make_map(enc, &mW1, d_in[4], DM, FF);
  make_map(enc, &mW3, d_in[5], DM, FF);
  make_map(enc, &mW2, d_in[6], FF, DM);
  cudaFuncSetAttribute(fused_kernel, cudaFuncAttributeMaxDynamicSharedMemorySize, SM_TOTAL);
  fused_kernel<<<128, NTHREADS, SM_TOTAL>>>(mQKV, mW1, mW3, mW2, mWO, (const bf16*)d_in[0], (bf16*)d_out, 0u);
}
```

```cpp
#include <cuda_runtime.h>
#include <cuda_bf16.h>
#include <cuda.h>
#include <stdint.h>

namespace {

typedef __nv_bfloat16 bf16;
constexpr int SEQ = 2048, DM = 512, FF = 1792;
constexpr int NTHREADS = 640;
constexpr int NSLOT = 5;
constexpr uint32_t POLYMASK = 0x57;

constexpr uint32_t SM_A     = 0;
constexpr uint32_t SM_RING  = 131072;
constexpr uint32_t SM_ONES  = SM_RING + 81920;
constexpr uint32_t SM_BIAS  = SM_ONES + 512;
constexpr uint32_t SM_MERGE = SM_BIAS + 2048;
constexpr uint32_t SM_RSTD  = SM_MERGE + 12288;
constexpr uint32_t SM_BAR   = SM_RSTD + 512;
constexpr uint32_t B_FULL1  = SM_BAR;
constexpr uint32_t B_EMPTY1 = B_FULL1 + 8 * 2 * NSLOT;
constexpr uint32_t B_KV     = B_EMPTY1 + 8 * NSLOT;
constexpr uint32_t B_FULL2  = B_KV + 64;
constexpr uint32_t B_OE     = B_FULL2 + 24;
constexpr uint32_t B_WO     = B_OE + 16;
constexpr uint32_t B_O      = B_WO + 8;
constexpr uint32_t B_EMPTY2 = B_O + 32;
constexpr uint32_t B_OEE    = B_EMPTY2 + 24;
constexpr uint32_t B_ADONE  = B_OEE + 16;
constexpr uint32_t SM_TOTAL = B_ADONE + 8;

__device__ __align__(1024) uint8_t gQ[32 * SEQ * 32];
__device__ __align__(1024) uint8_t gKV[32 * 16 * 8192];
__device__ __align__(1024) uint8_t gH[32 * 28 * 8192];
__device__ __align__(1024) uint8_t gO[32 * 8 * 8192];
__device__ uint32_t gFlag[72 * 32];
constexpr int F_QKV = 0, F_H = 8, F_O = 40;
#define TSTAMP(role, i)

template<int TB, int SD> __device__ __forceinline__ void wg_rs_n24(float* d, const uint32_t* a, uint64_t db) {
  if (SD)
    asm volatile("wgmma.mma_async.sync.aligned.m64n24k16.f32.bf16.bf16 {%0,%1,%2,%3,%4,%5,%6,%7,%8,%9,%10,%11}, {%12,%13,%14,%15}, %16, 1, 1, 1, %17;"
      : "+f"(d[0]),"+f"(d[1]),"+f"(d[2]),"+f"(d[3]),"+f"(d[4]),"+f"(d[5]),"+f"(d[6]),"+f"(d[7]),"+f"(d[8]),"+f"(d[9]),"+f"(d[10]),"+f"(d[11])
      : "r"(a[0]), "r"(a[1]), "r"(a[2]), "r"(a[3]), "l"(db), "n"(TB));
  else
    asm volatile("wgmma.mma_async.sync.aligned.m64n24k16.f32.bf16.bf16 {%0,%1,%2,%3,%4,%5,%6,%7,%8,%9,%10,%11}, {%12,%13,%14,%15}, %16, 0, 1, 1, %17;"
      : "=f"(d[0]),"=f"(d[1]),"=f"(d[2]),"=f"(d[3]),"=f"(d[4]),"=f"(d[5]),"=f"(d[6]),"=f"(d[7]),"=f"(d[8]),"=f"(d[9]),"=f"(d[10]),"=f"(d[11])
      : "r"(a[0]), "r"(a[1]), "r"(a[2]), "r"(a[3]), "l"(db), "n"(TB));
}
template<int TB, int SD> __device__ __forceinline__ void wg_rs_n64(float* d, const uint32_t* a, uint64_t db) {
  if (SD)
    asm volatile("wgmma.mma_async.sync.aligned.m64n64k16.f32.bf16.bf16 {%0,%1,%2,%3,%4,%5,%6,%7,%8,%9,%10,%11,%12,%13,%14,%15,%16,%17,%18,%19,%20,%21,%22,%23,%24,%25,%26,%27,%28,%29,%30,%31}, {%32,%33,%34,%35}, %36, 1, 1, 1, %37;"
      : "+f"(d[0]),"+f"(d[1]),"+f"(d[2]),"+f"(d[3]),"+f"(d[4]),"+f"(d[5]),"+f"(d[6]),"+f"(d[7]),"+f"(d[8]),"+f"(d[9]),"+f"(d[10]),"+f"(d[11]),"+f"(d[12]),"+f"(d[13]),"+f"(d[14]),"+f"(d[15]),"+f"(d[16]),"+f"(d[17]),"+f"(d[18]),"+f"(d[19]),"+f"(d[20]),"+f"(d[21]),"+f"(d[22]),"+f"(d[23]),"+f"(d[24]),"+f"(d[25]),"+f"(d[26]),"+f"(d[27]),"+f"(d[28]),"+f"(d[29]),"+f"(d[30]),"+f"(d[31])
      : "r"(a[0]), "r"(a[1]), "r"(a[2]), "r"(a[3]), "l"(db), "n"(TB));
  else
    asm volatile("wgmma.mma_async.sync.aligned.m64n64k16.f32.bf16.bf16 {%0,%1,%2,%3,%4,%5,%6,%7,%8,%9,%10,%11,%12,%13,%14,%15,%16,%17,%18,%19,%20,%21,%22,%23,%24,%25,%26,%27,%28,%29,%30,%31}, {%32,%33,%34,%35}, %36, 0, 1, 1, %37;"
      : "=f"(d[0]),"=f"(d[1]),"=f"(d[2]),"=f"(d[3]),"=f"(d[4]),"=f"(d[5]),"=f"(d[6]),"=f"(d[7]),"=f"(d[8]),"=f"(d[9]),"=f"(d[10]),"=f"(d[11]),"=f"(d[12]),"=f"(d[13]),"=f"(d[14]),"=f"(d[15]),"=f"(d[16]),"=f"(d[17]),"=f"(d[18]),"=f"(d[19]),"=f"(d[20]),"=f"(d[21]),"=f"(d[22]),"=f"(d[23]),"=f"(d[24]),"=f"(d[25]),"=f"(d[26]),"=f"(d[27]),"=f"(d[28]),"=f"(d[29]),"=f"(d[30]),"=f"(d[31])
      : "r"(a[0]), "r"(a[1]), "r"(a[2]), "r"(a[3]), "l"(db), "n"(TB));
}
template<int TB> __device__ __forceinline__ void wg_ss_n64(float* d, uint64_t da, uint64_t db) {
  asm volatile("wgmma.mma_async.sync.aligned.m64n64k16.f32.bf16.bf16 {%0,%1,%2,%3,%4,%5,%6,%7,%8,%9,%10,%11,%12,%13,%14,%15,%16,%17,%18,%19,%20,%21,%22,%23,%24,%25,%26,%27,%28,%29,%30,%31}, %32, %33, 1, 1, 1, 0, %34;"
    : "+f"(d[0]),"+f"(d[1]),"+f"(d[2]),"+f"(d[3]),"+f"(d[4]),"+f"(d[5]),"+f"(d[6]),"+f"(d[7]),"+f"(d[8]),"+f"(d[9]),"+f"(d[10]),"+f"(d[11]),"+f"(d[12]),"+f"(d[13]),"+f"(d[14]),"+f"(d[15]),"+f"(d[16]),"+f"(d[17]),"+f"(d[18]),"+f"(d[19]),"+f"(d[20]),"+f"(d[21]),"+f"(d[22]),"+f"(d[23]),"+f"(d[24]),"+f"(d[25]),"+f"(d[26]),"+f"(d[27]),"+f"(d[28]),"+f"(d[29]),"+f"(d[30]),"+f"(d[31])
    : "l"(da), "l"(db), "n"(TB));
}
template<int TB> __device__ __forceinline__ void wg_ss_n128(float* d, uint64_t da, uint64_t db) {
  asm volatile("wgmma.mma_async.sync.aligned.m64n128k16.f32.bf16.bf16 {%0,%1,%2,%3,%4,%5,%6,%7,%8,%9,%10,%11,%12,%13,%14,%15,%16,%17,%18,%19,%20,%21,%22,%23,%24,%25,%26,%27,%28,%29,%30,%31,%32,%33,%34,%35,%36,%37,%38,%39,%40,%41,%42,%43,%44,%45,%46,%47,%48,%49,%50,%51,%52,%53,%54,%55,%56,%57,%58,%59,%60,%61,%62,%63}, %64, %65, 1, 1, 1, 0, %66;"
    : "+f"(d[0]),"+f"(d[1]),"+f"(d[2]),"+f"(d[3]),"+f"(d[4]),"+f"(d[5]),"+f"(d[6]),"+f"(d[7]),"+f"(d[8]),"+f"(d[9]),"+f"(d[10]),"+f"(d[11]),"+f"(d[12]),"+f"(d[13]),"+f"(d[14]),"+f"(d[15]),"+f"(d[16]),"+f"(d[17]),"+f"(d[18]),"+f"(d[19]),"+f"(d[20]),"+f"(d[21]),"+f"(d[22]),"+f"(d[23]),"+f"(d[24]),"+f"(d[25]),"+f"(d[26]),"+f"(d[27]),"+f"(d[28]),"+f"(d[29]),"+f"(d[30]),"+f"(d[31]),"+f"(d[32]),"+f"(d[33]),"+f"(d[34]),"+f"(d[35]),"+f"(d[36]),"+f"(d[37]),"+f"(d[38]),"+f"(d[39]),"+f"(d[40]),"+f"(d[41]),"+f"(d[42]),"+f"(d[43]),"+f"(d[44]),"+f"(d[45]),"+f"(d[46]),"+f"(d[47]),"+f"(d[48]),"+f"(d[49]),"+f"(d[50]),"+f"(d[51]),"+f"(d[52]),"+f"(d[53]),"+f"(d[54]),"+f"(d[55]),"+f"(d[56]),"+f"(d[57]),"+f"(d[58]),"+f"(d[59]),"+f"(d[60]),"+f"(d[61]),"+f"(d[62]),"+f"(d[63])
    : "l"(da), "l"(db), "n"(TB));
}

__device__ __forceinline__ void wg_fence() { asm volatile("wgmma.fence.sync.aligned;" ::: "memory"); }
__device__ __forceinline__ void wg_commit() { asm volatile("wgmma.commit_group.sync.aligned;" ::: "memory"); }
template <int N> __device__ __forceinline__ void wg_wait() { asm volatile("wgmma.wait_group.sync.aligned %0;" ::"n"(N) : "memory"); }
template <int N> __device__ __forceinline__ void pin(float* r) {
#pragma unroll
  for (int i = 0; i < N; i++) asm volatile("" : "+f"(r[i])::"memory");
}
template <int N> __device__ __forceinline__ void clear(float* r) {
#pragma unroll
  for (int i = 0; i < N; i++) r[i] = 0.f;
  pin<N>(r);
}
template <int N> __device__ __forceinline__ void pin(uint32_t* r) {
#pragma unroll
  for (int i = 0; i < N; i++) asm volatile("" : "+r"(r[i])::"memory");
}
__device__ __forceinline__ uint64_t mkdesc(uint32_t addr, uint32_t lbo, uint32_t sbo, uint32_t swz) {
  return (uint64_t)((addr & 0x3FFFF) >> 4) | ((uint64_t)(lbo >> 4) << 16) | ((uint64_t)(sbo >> 4) << 32) | ((uint64_t)swz << 62);
}
__device__ __forceinline__ void mbar_init(uint32_t b, int c) { asm volatile("mbarrier.init.shared::cta.b64 [%0], %1;" ::"r"(b), "r"(c) : "memory"); }
__device__ __forceinline__ void mbar_expect(uint32_t b, int n) { asm volatile("mbarrier.arrive.expect_tx.shared::cta.b64 _, [%0], %1;" ::"r"(b), "r"(n) : "memory"); }
__device__ __forceinline__ void mbar_arrive(uint32_t b) { asm volatile("mbarrier.arrive.shared::cta.b64 _, [%0];" ::"r"(b) : "memory"); }
__device__ __forceinline__ bool mbar_try(uint32_t b, uint32_t ph) {
  uint32_t ok;
  asm volatile("{.reg .pred p; mbarrier.try_wait.parity.shared::cta.b64 p, [%1], %2; selp.u32 %0, 1, 0, p;}" : "=r"(ok) : "r"(b), "r"(ph) : "memory");
  return ok;
}
__device__ __forceinline__ void mbar_wait(uint32_t b, uint32_t ph) {
  if (mbar_try(b, ph)) return;
#pragma unroll 1
  for (int i = 0; i < (1 << 16); i++) {
    uint32_t ok;
    asm volatile("{.reg .pred p; mbarrier.try_wait.parity.shared::cta.b64 p, [%1], %2, 20000; selp.u32 %0, 1, 0, p;}" : "=r"(ok) : "r"(b), "r"(ph) : "memory");
    if (ok) return;
  }
  __trap();
}
__device__ __forceinline__ void bulk_load(uint32_t dst, const void* src, int bytes, uint32_t bar) {
  asm volatile("cp.async.bulk.shared::cluster.global.mbarrier::complete_tx::bytes [%0], [%1], %2, [%3];" ::"r"(dst), "l"(src), "r"(bytes), "r"(bar) : "memory");
}
__device__ __forceinline__ void tma_load(uint32_t dst, const CUtensorMap* m, int c0, int c1, uint32_t bar) {
  asm volatile("cp.async.bulk.tensor.2d.shared::cluster.global.mbarrier::complete_tx::bytes [%0], [%1, {%2, %3}], [%4];" ::"r"(dst), "l"(m), "r"(c0), "r"(c1), "r"(bar) : "memory");
}
__device__ __forceinline__ void tma_prefetch(const CUtensorMap* m, int c0, int c1) {
  asm volatile("cp.async.bulk.prefetch.tensor.2d.L2.global [%0, {%1, %2}];" ::"l"(m), "r"(c0), "r"(c1) : "memory");
}
__device__ __forceinline__ bool elect() {
  uint32_t r;
  asm volatile("{.reg .pred p; elect.sync _|p, 0xffffffff; selp.u32 %0, 1, 0, p;}" : "=r"(r));
  return r;
}
__device__ __forceinline__ void bar_sync(int id, int n) { asm volatile("bar.sync %0, %1;" ::"r"(id), "r"(n) : "memory"); }
__device__ __forceinline__ void bar_arrive(int id, int n) { asm volatile("bar.arrive %0, %1;" ::"r"(id), "r"(n) : "memory"); }
__device__ __forceinline__ bool bar_or(int id, int n, bool v) {
  uint32_t r;
  asm volatile("{.reg .pred p, q; setp.ne.u32 q, %3, 0; bar.red.or.pred p, %1, %2, q; selp.u32 %0, 1, 0, p;}" : "=r"(r) : "r"(id), "r"(n), "r"((uint32_t)v) : "memory");
  return r;
}
__device__ __forceinline__ void flag_add(int f) { asm volatile("red.release.gpu.global.add.u32 [%0], 1;" ::"l"(gFlag + f * 32) : "memory"); }
__device__ __forceinline__ void flag_wait(int f, uint32_t target, uint32_t ns) {
#pragma unroll 1
  for (int i = 0; i < (1 << 22); i++) {
    uint32_t v;
    asm volatile("ld.acquire.gpu.global.u32 %0, [%1];" : "=r"(v) : "l"(gFlag + f * 32) : "memory");
    if ((int)(v - target) >= 0) { asm volatile("fence.proxy.async.global;" ::: "memory"); return; }
    __nanosleep(ns);
  }
  __trap();
}
__device__ __forceinline__ float ex2(float x) { float y; asm("ex2.approx.ftz.f32 %0, %1;" : "=f"(y) : "f"(x)); return y; }
__device__ __forceinline__ float rcp(float x) { float y; asm("rcp.approx.ftz.f32 %0, %1;" : "=f"(y) : "f"(x)); return y; }
__device__ __forceinline__ uint32_t packbf(float lo, float hi) { uint32_t d; asm("cvt.rn.bf16x2.f32 %0, %1, %2;" : "=r"(d) : "f"(hi), "f"(lo)); return d; }
__device__ __forceinline__ float bfr(float x) { return __bfloat162float(__float2bfloat16(x)); }
__device__ __forceinline__ uint32_t hmul(uint32_t a, uint32_t b) { uint32_t d; asm("mul.rn.bf16x2 %0, %1, %2;" : "=r"(d) : "r"(a), "r"(b)); return d; }
__device__ __forceinline__ uint32_t hadd(uint32_t a, uint32_t b) { uint32_t d; asm("add.rn.bf16x2 %0, %1, %2;" : "=r"(d) : "r"(a), "r"(b)); return d; }
__device__ __forceinline__ uint32_t hsub(uint32_t a, uint32_t b) { uint32_t d; asm("sub.rn.bf16x2 %0, %1, %2;" : "=r"(d) : "r"(a), "r"(b)); return d; }
__device__ __forceinline__ void hmma(float* c, const uint4& a, uint32_t b0, uint32_t b1) {
  asm("mma.sync.aligned.m16n8k16.row.col.f32.bf16.bf16.f32 {%0,%1,%2,%3},{%4,%5,%6,%7},{%8,%9},{%0,%1,%2,%3};"
      : "+f"(c[0]), "+f"(c[1]), "+f"(c[2]), "+f"(c[3]) : "r"(a.x), "r"(a.y), "r"(a.z), "r"(a.w), "r"(b0), "r"(b1));
}
constexpr float LOG2E = 1.4426950408889634f;

__device__ __forceinline__ uint32_t exp_poly(float lo, float hi, uint32_t half2) {
  uint32_t u, mh, p;
  asm("cvt.pack.sat.s16.s32 %0, %1, %2;" : "=r"(u) : "r"(__float_as_uint(hi)), "r"(__float_as_uint(lo)));
  asm("lop3.b32 %0, %1, 0x007F007F, %2, 0xEA;" : "=r"(mh) : "r"(u), "r"(half2));
  asm("fma.rn.bf16x2 %0, %1, %2, %3;" : "=r"(p) : "r"(u), "r"(mh), "r"(u & 0xFF80FF80u));
  return p;
}
__device__ __forceinline__ void softmax64(float* s, uint32_t* p, uint32_t half2) {
  pin<32>(s);
#pragma unroll
  for (int j = 0; j < 8; j++) {
#pragma unroll
    for (int r = 0; r < 2; r++) {
      const float a = s[4 * j + 2 * r], b = s[4 * j + 2 * r + 1];
      p[2 * j + r] = ((POLYMASK >> j) & 1) ? exp_poly(a, b, half2) : packbf(ex2(a), ex2(b));
    }
  }
  pin<16>(p);
}

struct Tile { int kind, c0, c1; };
__device__ __forceinline__ Tile tile_of(int cg, int t) {
  const int c2 = cg >> 1;
  Tile r;
  if (cg & 1) {
    if (t == 0) { r.kind = 1; r.c0 = c2 * 128; r.c1 = r.c0 + 64; }
    else { r.kind = 2; r.c0 = r.c1 = (7 * c2 + 2 + t) * 64; }
  } else {
    if (t < 2) { r.kind = 0; r.c0 = 512 + c2 * 128 + t * 64; r.c1 = r.c0 + 512; }
    else { r.kind = 2; r.c0 = r.c1 = (7 * c2 + t - 2) * 64; }
  }
  return r;
}

__global__ void __launch_bounds__(NTHREADS, 1)
fused_kernel(const __grid_constant__ CUtensorMap mQKV, const __grid_constant__ CUtensorMap mW1, const __grid_constant__ CUtensorMap mW3,
             const __grid_constant__ CUtensorMap mW2, const __grid_constant__ CUtensorMap mWO, const __grid_constant__ CUtensorMap mX,
             const bf16* __restrict__ x, bf16* __restrict__ out,
             uint32_t zero) {
  extern __shared__ __align__(1024) uint8_t smem[];
  const uint32_t sb = (uint32_t)__cvta_generic_to_shared(smem);
  const int tid = threadIdx.x, lane = tid & 31, g = lane >> 2, t = lane & 3;
  const int warp = __shfl_sync(~0u, tid >> 5, 0), wg = warp >> 2, w = warp & 3;
  const int b = blockIdx.x;
  const int rb = b >> 3, cg = b & 7;
  const int head = b & 31, qb = b >> 5;
  const int rEarly = (rb >> 2) * 8 + ((0x3052 >> ((rb & 3) * 4)) & 7), rLate = (rb >> 2) * 8 + ((0x6741 >> ((rb & 3) * 4)) & 7);

  if (wg == 4) {
    asm volatile("setmaxnreg.dec.sync.aligned.u32 32;");
    if (w == 0) {
      uint32_t epoch;
      asm volatile("ld.relaxed.gpu.global.u32 %0, [%1];" : "=r"(epoch) : "l"(gFlag + F_O * 32) : "memory");
      if (lane < 2 * NSLOT) mbar_init(sb + B_FULL1 + 8 * lane, 1);
      if (lane < NSLOT) mbar_init(sb + B_EMPTY1 + 8 * lane, 8);
      if (lane < 24) mbar_init(sb + B_KV + 8 * lane, lane < 18 ? 1 : lane < 23 ? 4 : 12);
      asm volatile("fence.mbarrier_init.release.cluster;" ::: "memory");
      asm volatile("fence.proxy.async.shared::cta;" ::: "memory");
      __syncwarp();
      if (elect()) {
#pragma unroll
        for (int j = 0; j < 8; j++) {
          mbar_expect(sb + B_KV + 8 * j, 16384);
          tma_load(sb + SM_A + j * 16384, &mX, j * 64, rb * 128, sb + B_KV + 8 * j);
        }
      }
      bar_arrive(2, 544);
      epoch = (epoch >> 5) + 1;
      int slot = 0;
      uint32_t ph = 1;
#pragma unroll 1
      for (int tI = 0; tI < 5; tI++) {
        const Tile tl = tile_of(cg, tI);
        const CUtensorMap *m0 = tl.kind == 2 ? &mW1 : &mQKV, *m1 = tl.kind == 2 ? &mW3 : &mQKV;
#pragma unroll 1
        for (int k = 0; k < 8; k++) {
          const uint32_t full = sb + B_FULL1 + 8 * ((tI & 1) * NSLOT + slot), dst = sb + SM_RING + slot * 16384;
          if (tI == 4 && k == 0) flag_wait(F_QKV + (head >> 2), epoch * 32, 32);
          if (tI == 0 && k == NSLOT) {
            const int i = 2 * NSLOT + rb + lane * 16;
            if (i < 80) {
              const Tile tp = tile_of(cg, i >> 4);
              tma_prefetch((i & 1) ? (tp.kind == 2 ? &mW3 : &mQKV) : (tp.kind == 2 ? &mW1 : &mQKV), (i & 1) ? tp.c1 : tp.c0, ((i >> 1) & 7) * 64);
            }
            __syncwarp();
          }
          mbar_wait(sb + B_EMPTY1 + 8 * slot, ph);
          if (elect()) {
            mbar_expect(full, 16384);
            tma_load(dst, m0, tl.c0, k * 64, full);
            tma_load(dst + 8192, m1, tl.c1, k * 64, full);
          }
          if (++slot == NSLOT) { slot = 0; ph ^= 1; }
        }
      }
#pragma unroll 1
      for (int j = 0; j < 8; j++) {
        if (j >= 8 - NSLOT) {
          mbar_wait(sb + B_EMPTY1 + 8 * slot, ph);
          if (++slot == NSLOT) { slot = 0; ph ^= 1; }
        }
        if (elect()) {
          mbar_expect(sb + B_KV + 8 * j, 16384);
          bulk_load(sb + SM_A + j * 16384, gKV + (size_t)head * 131072 + j * 16384, 16384, sb + B_KV + 8 * j);
        }
      }
      flag_wait(F_H + rEarly, epoch * 28, 100);
      flag_wait(F_H + rLate, epoch * 28, 100);
      slot = 0; ph = 1;
#pragma unroll 1
      for (int n = 0; n < 31; n++) {
        const uint32_t full = sb + B_FULL2 + 8 * slot, dst = sb + SM_RING + slot * 24576;
        mbar_wait(sb + B_EMPTY2 + 8 * slot, ph);
        if (n < 28 && elect()) {
          mbar_expect(full, 24576);
          tma_load(dst, &mW2, cg * 64, n * 64, full);
          bulk_load(dst + 8192, gH + (size_t)(rEarly * 28 + n) * 8192, 8192, full);
          bulk_load(dst + 16384, gH + (size_t)(rLate * 28 + n) * 8192, 8192, full);
        }
        if (++slot == 3) { slot = 0; ph ^= 1; }
      }
      if (elect()) {
        mbar_expect(sb + B_WO, 65536);
#pragma unroll 1
        for (int k = 0; k < 8; k++) tma_load(sb + SM_RING + k * 8192, &mWO, cg * 64, k * 64, sb + B_WO);
      }
      flag_wait(F_O + rEarly, epoch * 32, 200);
#pragma unroll 1
      for (int n = 0; n < 8; n++) {
        mbar_wait(sb + B_OEE + 8 * (n & 1), ((n >> 1) & 1) ^ 1);
        if (elect()) {
          mbar_expect(sb + B_OE + 8 * (n & 1), 8192);
          bulk_load(sb + SM_RING + 65536 + (n & 1) * 8192, gO + (size_t)(rEarly * 8 + n) * 8192, 8192, sb + B_OE + 8 * (n & 1));
        }
      }
      mbar_wait(sb + B_ADONE, 0);
      flag_wait(F_O + rLate, epoch * 32, 20);
      if (elect()) {
#pragma unroll
        for (int i = 0; i < 4; i++) {
          mbar_expect(sb + B_O + 8 * i, 16384);
          bulk_load(sb + SM_A + i * 16384, gO + (size_t)rLate * 65536 + i * 16384, 16384, sb + B_O + 8 * i);
        }
      }
    } else {
      if (w < 3) {
#pragma unroll 1
        for (int tI = w - 1; tI < 5; tI += 2) {
          const Tile tl = tile_of(cg, tI);
          bar_sync(3 + w, 288);
          if (lane < (tl.kind ? 2 : 1)) flag_add(tl.kind == 2 ? F_H + rb * 2 + lane : F_QKV + ((tl.c0 >> 6) & 7) + lane);
          __syncwarp();
        }
      }
#pragma unroll 1
      for (int i = 0; i < (w == 2 ? 2 : 3); i++) {
        bar_sync(12 + w, 160);
        if (lane == 0) flag_add(F_O + qb * 8 + (((w == 1 ? 0x102 : w == 2 ? 0x43 : 0x765) >> (i * 4)) & 7));
        __syncwarp();
      }
    }
    return;
  }

  TSTAMP(wg, 0);
  asm volatile("setmaxnreg.inc.sync.aligned.u32 112;");

  {
    if (tid < 128) ((uint32_t*)(smem + SM_ONES))[tid] = 0x3F803F80u;
    {
      const int n = tid >> 3, k = (tid & 7) * 2;
      const bool poly = (POLYMASK >> (n >> 3)) & 1;
      const float cm = -127.f + 0.5849625f - 0.0020f, chi = bfr(cm), clo = cm - chi, sc = poly ? 0x1p-71f : 0x1p71f;
      float v0 = 0.f, v1 = 0.f;
      if (k == 0) { v0 = sc; v1 = sc; }
      if (k == 2) { v0 = sc; v1 = poly ? 0.f : chi * sc; }
      if (k == 4) { v0 = poly ? 0.f : clo * sc; }
      *(uint32_t*)(smem + SM_BIAS + n * 32 + (((k >> 3) ^ ((n >> 2) & 1)) << 4) + (k & 7) * 2) = packbf(v0, v1);
    }
    float cs[4] = {0.f, 0.f, 0.f, 0.f}, ca[4] = {0.f, 0.f, 0.f, 0.f}, cb[4] = {0.f, 0.f, 0.f, 0.f};
    uint4 xv[16];
    const int row = warp * 8 + g;
    uint8_t* xs = smem + SM_A + row * 128;
    const int xo0 = (((4 * (g & 1) + t) ^ g) << 4), xo1 = xo0 ^ 64;
    bar_sync(2, 544);
#pragma unroll
    for (int j = 0; j < 16; j++) {
      if ((j & 1) == 0) mbar_wait(sb + B_KV + 4 * j, 0);
      xv[j] = *(const uint4*)(xs + (j >> 1) * 16384 + ((j & 1) ? xo1 : xo0));
      hmma(cs, xv[j], 0x3F803F80u, 0x3F803F80u);
      hmma(ca, xv[j], xv[j].x, xv[j].z);
      hmma(cb, xv[j], xv[j].y, xv[j].w);
    }
    const float mean = (cs[0] + cs[2]) * (1.f / DM);
    const uint32_t m2 = packbf(mean, mean);
    if (m2 != 0x12345678) TSTAMP(4, wg);
#pragma unroll
    for (int j = 0; j < 16; j++)
      *(uint4*)(xs + (j >> 1) * 16384 + ((j & 1) ? xo1 : xo0)) = make_uint4(hsub(xv[j].x, m2), hsub(xv[j].y, m2), hsub(xv[j].z, m2), hsub(xv[j].w, m2));
    {
      const float var = fmaxf(((g & 1) ? ca[1] + cb[3] : ca[0] + cb[2]) * (1.f / DM) - mean * mean, 0.f);
      float sd;
      asm("sqrt.approx.f32 %0, %1;" : "=f"(sd) : "f"(bfr(bfr(var) + 1e-5f)));
      if (t == (g >> 1)) ((float*)(smem + SM_RSTD))[row] = rcp(bfr(sd));
    }
    TSTAMP(4, 4 + wg);
    asm volatile("fence.proxy.async.shared::cta;" ::: "memory");
    bar_sync(1, 512);
  }
  TSTAMP(wg, 1);
  const int pair = wg >> 1, half = wg & 1;

  {
    uint32_t par = 0;
    const uint64_t dA0 = mkdesc(sb + SM_A + half * 8192, 16, 1024, 1), dB0 = mkdesc(sb + SM_RING, 8192, 1024, 1);
#pragma unroll 1
    for (int tI = pair; tI < 5; tI += 2) {
      float acc[64];
      clear<64>(acc);
      int slot = (tI * 8) % NSLOT, prev = 0;
#pragma unroll 1
      for (int k = 0; k < 8; k++) {
        mbar_wait(sb + B_FULL1 + 8 * (pair * NSLOT + slot), (par >> slot) & 1);
        par ^= 1u << slot;
        if (tI == 0 && wg == 0) TSTAMP(4, 8 + k);
        const uint64_t dA = dA0 + k * 1024, dB = dB0 + slot * 1024;
        wg_fence();
        wg_ss_n128<1>(acc, dA, dB);
        wg_ss_n128<1>(acc, dA + 2, dB + 128);
        wg_ss_n128<1>(acc, dA + 4, dB + 256);
        wg_ss_n128<1>(acc, dA + 6, dB + 384);
        wg_commit();
        if (k > 0) {
          wg_wait<1>();
          if (lane == 0) mbar_arrive(sb + B_EMPTY1 + 8 * prev);
        }
        prev = slot;
        if (++slot == NSLOT) slot = 0;
      }
      wg_wait<0>();
      if (lane == 0) mbar_arrive(sb + B_EMPTY1 + 8 * prev);
      pin<64>(acc);
      TSTAMP(wg, 2 + (tI >> 1) * 2);
      const Tile tl = tile_of(cg, tI);
      const int lrow = half * 64 + w * 16 + g;
      const float r0 = ((const float*)(smem + SM_RSTD))[lrow], r1 = ((const float*)(smem + SM_RSTD))[lrow + 8];
      if (tl.kind == 2) {
        uint32_t* hp = (uint32_t*)(gH + (size_t)((rb * 2 + half) * 28 + (tl.c0 >> 6)) * 8192 + w * 256) + lane;
#pragma unroll
        for (int j = 0; j < 8; j++) {
#pragma unroll
          for (int r = 0; r < 2; r++) {
            const float rs = r ? r1 : r0, e = -LOG2E * rs, q = rs * rs;
            const float g0 = acc[4 * j + 2 * r], g1 = acc[4 * j + 2 * r + 1];
            const float h0 = (g0 * q) * acc[32 + 4 * j + 2 * r] * rcp(1.f + ex2(g0 * e));
            const float h1 = (g1 * q) * acc[33 + 4 * j + 2 * r] * rcp(1.f + ex2(g1 * e));
            hp[j * 256 + r * 32] = packbf(h0, h1);
          }
        }
      } else {
        const int hg = (tl.c0 >> 6) & 7;
#pragma unroll
        for (int u = 0; u < 2; u++) {
#pragma unroll
          for (int r = 0; r < 2; r++) {
            float sc = r ? r1 : r0;
            uint8_t* p;
            size_t hs;
            if (tl.kind == 1) {
              sc *= 0.25f * LOG2E * 0x1p-71f;
              p = gQ + (size_t)(hg + u) * 4 * 65536 + (size_t)(rb * 128 + lrow + r * 8) * 32 + t * 8;
              hs = 65536;
            } else {
              if (u == 0) sc *= ((POLYMASK >> (2 * w + r)) & 1) ? 0x1p-71f : 0x1p71f;
              p = gKV + (size_t)hg * 4 * 131072 + rb * 8192 + u * 4096 + (lrow + r * 8) * 32 + ((t * 8) ^ ((g & 4) << 2));
              hs = 131072;
            }
#pragma unroll
            for (int hh = 0; hh < 4; hh++) {
              const float* a = acc + u * 32 + hh * 8 + 2 * r;
              *(uint2*)(p + hh * hs) = make_uint2(packbf(a[0] * sc, a[1] * sc), packbf(a[4] * sc, a[5] * sc));
            }
          }
        }
      }
      bar_arrive(4 + pair, 288);
      TSTAMP(wg, 3 + (tI >> 1) * 2);
    }
  }

  if (wg < 3) {
    constexpr uint64_t VS = (uint64_t)(32 - (32LL << 16));
    const uint32_t half2 = 0x3F003F00u + zero;
    const uint64_t dBias = mkdesc(sb + SM_BIAS, 16, 256, 3);
    const int nseg = wg == 1 ? 4 : 3;
    const uint32_t segs = wg == 0 ? 0x102 : wg == 1 ? 0x4352 : 0x765;
    int ready = wg == 0 ? 2 : 0;
    mbar_wait(sb + B_KV + 8 * ready, 1);
    const uint8_t* qbase = gQ + (size_t)head * 65536 + (size_t)(qb * 512 + w * 16 + g) * 32 + t * 4;
    uint32_t q[4], qn[4];
    auto load_q = [&](int seg) {
      const uint32_t* qp = (const uint32_t*)(qbase + ((segs >> (seg * 4)) & 7) * 2048);
      qn[0] = __ldcg(qp); qn[1] = __ldcg(qp + 64); qn[2] = __ldcg(qp + 4); qn[3] = __ldcg(qp + 68);
    };
    load_q(0);
    TSTAMP(wg, 8);
    bool exact = false;
#pragma unroll 1
    for (int seg = 0; seg < nseg; seg++) {
      int c0 = 0, c1 = 16, mode = 0;
      if (wg == 1) { if (seg < 2) { c0 = seg * 11; c1 = c0 + 5; mode = 1; } }
      else if (seg == 0) { c0 = wg ? 0 : 5; c1 = c0 + 11; mode = 2; }
      const int rbl = (segs >> (seg * 4)) & 7, rblk = qb * 8 + rbl;
      if ((seg > 0 || exact) && ready < 8) {
#pragma unroll 1
        for (int j = 0; j < 8; j++) mbar_wait(sb + B_KV + 8 * j, 1);
        ready = 8;
      }
      uint32_t qa[4];
      if (!exact) {
#pragma unroll
        for (int i = 0; i < 4; i++) q[i] = qn[i];
        load_q(seg + 1);
      }
      if (seg == nseg - 1 && q[0] != 0x12345678) TSTAMP(wg, 13);
      const uint32_t va = sb + SM_A + 4096 + c0 * 8192;
      const uint64_t dV0 = mkdesc(va, sb + SM_ONES - va, 256, 3);
      float o[12], bias[2];
      {
        const int nmax = exact ? (c1 - c0) * 2 : 1;
        float s[32];
        uint32_t p0[16], p1[16];
        float mp0 = -INFINITY, mp1 = -INFINITY, mm0 = -INFINITY, mm1 = -INFINITY;
#pragma unroll 1
        for (int i = 0; i < nmax; i++) {
          wg_fence();
          wg_rs_n64<0, 0>(s, q, dV0 - 256 + (i >> 1) * 512 + (i & 1) * 128);
          wg_commit();
          wg_wait<0>();
          pin<32>(s);
#pragma unroll
          for (int j = 0; j < 8; j++) {
            if ((POLYMASK >> j) & 1) { mp0 = fmaxf(mp0, fmaxf(s[4 * j], s[4 * j + 1])); mp1 = fmaxf(mp1, fmaxf(s[4 * j + 2], s[4 * j + 3])); }
            else { mm0 = fmaxf(mm0, fmaxf(s[4 * j], s[4 * j + 1])); mm1 = fmaxf(mm1, fmaxf(s[4 * j + 2], s[4 * j + 3])); }
          }
        }
#pragma unroll
        for (int r = 0; r < 2; r++) {
          float v = fmaxf(r ? mm1 : mm0, ((r ? mp1 : mp0) * 0x1p71f) * 0x1p71f);
          v = fmaxf(v, __shfl_xor_sync(~0u, v, 1));
          v = fmaxf(v, __shfl_xor_sync(~0u, v, 2));
          bias[r] = rintf(64.f - v);
          const float y = bias[r] * 0x1p-71f, hi = bfr(y), mid = bfr(y - hi);
          qa[r] = t == 0 ? packbf(hi, mid) : t == 1 ? packbf(y - hi - mid, 0x1p-71f) : t == 2 ? 0x00001C00u : 0u;
          qa[2 + r] = qa[r] & zero;
        }
        if (seg == nseg - 1 && qa[0] != 0x12345678) TSTAMP(wg, 14);
        clear<12>(o);
        uint64_t c = dV0;
        wg_fence();
        wg_rs_n64<0, 0>(s, qa, dBias);
        wg_rs_n64<0, 1>(s, q, c - 256);
        wg_commit();
        wg_wait<0>();
        if (seg == nseg - 1) TSTAMP(wg, 15);
#pragma unroll 1
        for (int ci = c0; ci < c1;) {
        if (ready < 7) mbar_wait(sb + B_KV + 8 * ++ready, 1);
        ci = ready >= 7 ? c1 : min(c1, 2 * ready);
        const uint32_t cend = (uint32_t)(dV0 + (uint64_t)(ci - c0) * 16 * VS);
#pragma unroll 1
        do {
          softmax64(s, p0, half2);
          wg_fence();
          wg_rs_n64<0, 0>(s, qa, dBias);
          wg_rs_n64<0, 1>(s, q, c - 128);
          wg_commit();
#pragma unroll
          for (int k = 0; k < 4; k++) wg_rs_n24<1, 1>(o, p0 + 4 * k, c + k * VS);
          wg_commit();
          wg_wait<1>();
          softmax64(s, p1, half2);
          wg_fence();
          wg_rs_n64<0, 0>(s, qa, dBias);
          wg_rs_n64<0, 1>(s, q, c + 256);
          wg_commit();
#pragma unroll
          for (int k = 0; k < 4; k++) wg_rs_n24<1, 1>(o, p1 + 4 * k, c + (4 + k) * VS);
          wg_commit();
          c += 16 * VS;
          wg_wait<1>();
        } while ((uint32_t)c != cend);
        }
        wg_wait<0>();
        pin<12>(o);
      }
      exact = __all_sync(~0u, bar_or(10 + wg, 128, !exact && !(o[8] < 0x1p90f && o[10] < 0x1p90f)));
      if (exact) { seg--; continue; }
      if (mode == 1) {
        float* mp = (float*)(smem + SM_MERGE + seg * 6144) + (tid & 127);
        o[9] = bias[0]; o[11] = bias[1];
#pragma unroll
        for (int i = 0; i < 12; i++) mp[i * 128] = o[i];
        bar_arrive(8 + seg, 256);
        continue;
      }
      if (mode == 2) {
        const float* mp = (const float*)(smem + SM_MERGE + (wg >> 1) * 6144) + (tid & 127);
        bar_sync(8 + (wg >> 1), 256);
#pragma unroll
        for (int r = 0; r < 2; r++) {
          const float bo = mp[(9 + 2 * r) * 128], bm = fminf(bo, bias[r]);
          const float fa = ex2(0.5f * (bm - bias[r])), fb = ex2(0.5f * (bm - bo));
          o[2 * r] = o[2 * r] * fa * fa + mp[(2 * r) * 128] * fb * fb;
          o[2 * r + 1] = o[2 * r + 1] * fa * fa + mp[(2 * r + 1) * 128] * fb * fb;
          o[4 + 2 * r] = o[4 + 2 * r] * fa * fa + mp[(4 + 2 * r) * 128] * fb * fb;
          o[5 + 2 * r] = o[5 + 2 * r] * fa * fa + mp[(5 + 2 * r) * 128] * fb * fb;
          o[8 + 2 * r] = o[8 + 2 * r] * fa * fa + mp[(8 + 2 * r) * 128] * fb * fb;
        }
      }
      if (seg == nseg - 1 && lane == 0) mbar_arrive(sb + B_ADONE);
#pragma unroll
      for (int r = 0; r < 2; r++) {
        const float inv = rcp(o[8 + 2 * r]);
        const uint32_t a = packbf(o[2 * r] * inv, o[2 * r + 1] * inv), c = packbf(o[4 + 2 * r] * inv, o[5 + 2 * r] * inv);
        const uint32_t e = __shfl_xor_sync(~0u, (t & 2) ? a : c, 2);
        *(uint2*)(gO + (size_t)(rblk * 8 + (head >> 2)) * 8192 + ((head & 3) * 2 + (t & 1)) * 1024 + (2 * w + r) * 128 + g * 16 + (t & 2) * 4) =
            (t & 2) ? make_uint2(e, c) : make_uint2(a, e);
      }
      bar_arrive(13 + wg, 160);
      TSTAMP(wg, 9 + seg);
    }
  } else {
    uint32_t gate[32];
    const uint64_t dB0 = mkdesc(sb + SM_RING, 8192, 1024, 1);
    {
      const uint64_t dA0 = mkdesc(sb + SM_RING + 8192, 1024, 128, 0);
      float acc[64];
      clear<64>(acc);
      int slot = 0;
      uint32_t ph = 0;
#pragma unroll 1
      for (int n = 0; n < 28; n++) {
        mbar_wait(sb + B_FULL2 + 8 * slot, ph);
        const uint64_t dA = dA0 + slot * 1536, dB = dB0 + slot * 1536;
        wg_fence();
#pragma unroll
        for (int k = 0; k < 4; k++) {
          wg_ss_n64<1>(acc, dA + k * 128, dB + k * 128);
          wg_ss_n64<1>(acc + 32, dA + 512 + k * 128, dB + k * 128);
        }
        wg_commit();
        wg_wait<0>();
        if (lane == 0) mbar_arrive(sb + B_EMPTY2 + 8 * slot);
        if (++slot == 3) { slot = 0; ph ^= 1; }
      }
      pin<64>(acc);
#pragma unroll
      for (int i = 0; i < 32; i++) {
        const float f0 = bfr(acc[2 * i]), f1 = bfr(acc[2 * i + 1]);
        gate[i] = packbf(f0 * rcp(1.f + ex2(-LOG2E * f0)), f1 * rcp(1.f + ex2(-LOG2E * f1)));
      }
    }
    TSTAMP(wg, 8);
#pragma unroll
    for (int pass = 0; pass < 2; pass++) {
      const size_t off = (size_t)((pass ? rLate : rEarly) * 64 + w * 16 + g) * DM + cg * 64 + (t & 1) * 8 + (t & 2) * 2;
      uint2 xr[8];
#pragma unroll
      for (int i = 0; i < 8; i++) xr[i] = __ldg((const uint2*)(x + off + (i & 1) * 8 * DM + (i >> 1) * 16));
      float acc[32];
      clear<32>(acc);
      if (pass == 0) {
        const uint64_t dA0 = mkdesc(sb + SM_RING + 65536, 1024, 128, 0);
        mbar_wait(sb + B_WO, 0);
#pragma unroll 1
        for (int n = 0; n < 8; n++) {
          mbar_wait(sb + B_OE + 8 * (n & 1), (n >> 1) & 1);
          wg_fence();
#pragma unroll
          for (int k = 0; k < 4; k++) wg_ss_n64<1>(acc, dA0 + (n & 1) * 512 + k * 128, dB0 + n * 512 + k * 128);
          wg_commit();
          wg_wait<0>();
          if (lane == 0) mbar_arrive(sb + B_OEE + 8 * (n & 1));
        }
      } else {
        mbar_wait(sb + B_ADONE, 0);
        const uint64_t dA = mkdesc(sb + SM_A, 1024, 128, 0);
#pragma unroll 1
        for (int n = 0; n < 4; n++) {
          mbar_wait(sb + B_O + 8 * n, 0);
          wg_fence();
#pragma unroll
          for (int k = 0; k < 8; k++) wg_ss_n64<1>(acc, dA + (n * 8 + k) * 128, dB0 + (n * 8 + k) * 128);
          wg_commit();
        }
        wg_wait<0>();
      }
      pin<32>(acc);
      TSTAMP(wg, 9 + 2 * pass);
#pragma unroll
      for (int i = 0; i < 8; i++) {
        const int ia = (i >> 1) * 4 + (i & 1), ib = ia + 2;
        const uint32_t ya = hmul(packbf(acc[2 * ia], acc[2 * ia + 1]), gate[pass * 16 + ia]);
        const uint32_t yb = hmul(packbf(acc[2 * ib], acc[2 * ib + 1]), gate[pass * 16 + ib]);
        const uint32_t e = __shfl_xor_sync(~0u, (t & 1) ? ya : yb, 1);
        const uint32_t lo = (t & 1) ? e : ya, hi = (t & 1) ? yb : e;
        *(uint2*)(out + off + (i & 1) * 8 * DM + (i >> 1) * 16) = make_uint2(hadd(xr[i].x, lo), hadd(xr[i].y, hi));
      }
      TSTAMP(wg, 10 + 2 * pass);
    }
  }
}

typedef CUresult (*EncodeFn)(CUtensorMap*, CUtensorMapDataType, cuuint32_t, void*, const cuuint64_t*, const cuuint64_t*, const cuuint32_t*,
                             const cuuint32_t*, CUtensorMapInterleave, CUtensorMapSwizzle, CUtensorMapL2promotion, CUtensorMapFloatOOBfill);

void make_map(EncodeFn enc, CUtensorMap* m, void* p, int rows, int cols, int boxrows = 64) {
  const cuuint64_t dims[2] = {(cuuint64_t)cols, (cuuint64_t)rows}, strides[1] = {(cuuint64_t)cols * 2};
  const cuuint32_t box[2] = {64, (cuuint32_t)boxrows}, es[2] = {1, 1};
  enc(m, CU_TENSOR_MAP_DATA_TYPE_BFLOAT16, 2, p, dims, strides, box, es, CU_TENSOR_MAP_INTERLEAVE_NONE, CU_TENSOR_MAP_SWIZZLE_128B,
      CU_TENSOR_MAP_L2_PROMOTION_L2_128B, CU_TENSOR_MAP_FLOAT_OOB_FILL_NONE);
}

}

extern "C" void kernel_launch(void* const* d_in, const int* in_sizes, int n_in, void* d_out, int out_size) {
  (void)in_sizes; (void)n_in; (void)out_size;
  void* fn = nullptr;
  cudaDriverEntryPointQueryResult qr;
  cudaGetDriverEntryPoint("cuTensorMapEncodeTiled", &fn, cudaEnableDefault, &qr);
  EncodeFn enc = (EncodeFn)fn;
  CUtensorMap mQKV, mW1, mW3, mW2, mWO, mX;
  make_map(enc, &mX, d_in[0], SEQ, DM, 128);
  make_map(enc, &mQKV, d_in[1], DM, 3 * DM);
  make_map(enc, &mWO, d_in[2], DM, DM);
  make_map(enc, &mW1, d_in[4], DM, FF);
  make_map(enc, &mW3, d_in[5], DM, FF);
  make_map(enc, &mW2, d_in[6], FF, DM);
  cudaFuncSetAttribute(fused_kernel, cudaFuncAttributeMaxDynamicSharedMemorySize, SM_TOTAL);
  fused_kernel<<<128, NTHREADS, SM_TOTAL>>>(mQKV, mW1, mW3, mW2, mWO, mX, (const bf16*)d_in[0], (bf16*)d_out, 0u);
}
```

```cpp
#include <cuda_runtime.h>
#include <cuda_bf16.h>
#include <cuda.h>
#include <stdint.h>

namespace {

typedef __nv_bfloat16 bf16;
constexpr int SEQ = 2048, DM = 512, FF = 1792;
constexpr int NTHREADS = 640;
constexpr int NSLOT = 5;
constexpr uint32_t POLYMASK = 0x57;

constexpr uint32_t SM_A     = 0;
constexpr uint32_t SM_RING  = 131072;
constexpr uint32_t SM_ONES  = SM_RING + 81920;
constexpr uint32_t SM_BIAS  = SM_ONES + 512;
constexpr uint32_t SM_MERGE = SM_BIAS + 2048;
constexpr uint32_t SM_RSTD  = SM_MERGE + 12288;
constexpr uint32_t SM_SHIFT = SM_RSTD + 512;
constexpr uint32_t SM_BAR   = SM_SHIFT + 2048;
constexpr uint32_t B_FULL1  = SM_BAR;
constexpr uint32_t B_EMPTY1 = B_FULL1 + 8 * 2 * NSLOT;
constexpr uint32_t B_KV     = B_EMPTY1 + 8 * NSLOT;
constexpr uint32_t B_FULL2  = B_KV + 64;
constexpr uint32_t B_OE     = B_FULL2 + 24;
constexpr uint32_t B_WO     = B_OE + 16;
constexpr uint32_t B_O      = B_WO + 8;
constexpr uint32_t B_EMPTY2 = B_O + 32;
constexpr uint32_t B_OEE    = B_EMPTY2 + 24;
constexpr uint32_t B_ADONE  = B_OEE + 16;
constexpr uint32_t B_K0     = B_ADONE + 8;
constexpr uint32_t B_SHIFT  = B_K0 + 8;
constexpr uint32_t SM_TOTAL = B_SHIFT + 8;
static_assert(SM_TOTAL <= 232448, "shared memory");

__device__ __align__(1024) uint8_t gQ[32 * SEQ * 32];
__device__ __align__(1024) uint8_t gKV[32 * 16 * 8192];
__device__ __align__(1024) uint8_t gH[32 * 28 * 8192];
__device__ __align__(1024) uint8_t gO[32 * 8 * 8192];
__device__ uint32_t gFlag[72 * 32];
constexpr int F_QKV = 0, F_H = 8, F_O = 40;
#define TSTAMP(role, i)

template<int TB, int SD> __device__ __forceinline__ void wg_rs_n24(float* d, const uint32_t* a, uint64_t db) {
  if (SD)
    asm volatile("wgmma.mma_async.sync.aligned.m64n24k16.f32.bf16.bf16 {%0,%1,%2,%3,%4,%5,%6,%7,%8,%9,%10,%11}, {%12,%13,%14,%15}, %16, %18, 1, 1, %17;"
      : "+f"(d[0]),"+f"(d[1]),"+f"(d[2]),"+f"(d[3]),"+f"(d[4]),"+f"(d[5]),"+f"(d[6]),"+f"(d[7]),"+f"(d[8]),"+f"(d[9]),"+f"(d[10]),"+f"(d[11])
      : "r"(a[0]), "r"(a[1]), "r"(a[2]), "r"(a[3]), "l"(db), "n"(TB), "n"(SD & 1));
  else
    asm volatile("wgmma.mma_async.sync.aligned.m64n24k16.f32.bf16.bf16 {%0,%1,%2,%3,%4,%5,%6,%7,%8,%9,%10,%11}, {%12,%13,%14,%15}, %16, 0, 1, 1, %17;"
      : "=f"(d[0]),"=f"(d[1]),"=f"(d[2]),"=f"(d[3]),"=f"(d[4]),"=f"(d[5]),"=f"(d[6]),"=f"(d[7]),"=f"(d[8]),"=f"(d[9]),"=f"(d[10]),"=f"(d[11])
      : "r"(a[0]), "r"(a[1]), "r"(a[2]), "r"(a[3]), "l"(db), "n"(TB));
}
template<int TB, int SD> __device__ __forceinline__ void wg_rs_n64(float* d, const uint32_t* a, uint64_t db) {
  if (SD)
    asm volatile("wgmma.mma_async.sync.aligned.m64n64k16.f32.bf16.bf16 {%0,%1,%2,%3,%4,%5,%6,%7,%8,%9,%10,%11,%12,%13,%14,%15,%16,%17,%18,%19,%20,%21,%22,%23,%24,%25,%26,%27,%28,%29,%30,%31}, {%32,%33,%34,%35}, %36, %38, 1, 1, %37;"
      : "+f"(d[0]),"+f"(d[1]),"+f"(d[2]),"+f"(d[3]),"+f"(d[4]),"+f"(d[5]),"+f"(d[6]),"+f"(d[7]),"+f"(d[8]),"+f"(d[9]),"+f"(d[10]),"+f"(d[11]),"+f"(d[12]),"+f"(d[13]),"+f"(d[14]),"+f"(d[15]),"+f"(d[16]),"+f"(d[17]),"+f"(d[18]),"+f"(d[19]),"+f"(d[20]),"+f"(d[21]),"+f"(d[22]),"+f"(d[23]),"+f"(d[24]),"+f"(d[25]),"+f"(d[26]),"+f"(d[27]),"+f"(d[28]),"+f"(d[29]),"+f"(d[30]),"+f"(d[31])
      : "r"(a[0]), "r"(a[1]), "r"(a[2]), "r"(a[3]), "l"(db), "n"(TB), "n"(SD & 1));
  else
    asm volatile("wgmma.mma_async.sync.aligned.m64n64k16.f32.bf16.bf16 {%0,%1,%2,%3,%4,%5,%6,%7,%8,%9,%10,%11,%12,%13,%14,%15,%16,%17,%18,%19,%20,%21,%22,%23,%24,%25,%26,%27,%28,%29,%30,%31}, {%32,%33,%34,%35}, %36, 0, 1, 1, %37;"
      : "=f"(d[0]),"=f"(d[1]),"=f"(d[2]),"=f"(d[3]),"=f"(d[4]),"=f"(d[5]),"=f"(d[6]),"=f"(d[7]),"=f"(d[8]),"=f"(d[9]),"=f"(d[10]),"=f"(d[11]),"=f"(d[12]),"=f"(d[13]),"=f"(d[14]),"=f"(d[15]),"=f"(d[16]),"=f"(d[17]),"=f"(d[18]),"=f"(d[19]),"=f"(d[20]),"=f"(d[21]),"=f"(d[22]),"=f"(d[23]),"=f"(d[24]),"=f"(d[25]),"=f"(d[26]),"=f"(d[27]),"=f"(d[28]),"=f"(d[29]),"=f"(d[30]),"=f"(d[31])
      : "r"(a[0]), "r"(a[1]), "r"(a[2]), "r"(a[3]), "l"(db), "n"(TB));
}
template<int TB> __device__ __forceinline__ void wg_ss_n64(float* d, uint64_t da, uint64_t db) {
  asm volatile("wgmma.mma_async.sync.aligned.m64n64k16.f32.bf16.bf16 {%0,%1,%2,%3,%4,%5,%6,%7,%8,%9,%10,%11,%12,%13,%14,%15,%16,%17,%18,%19,%20,%21,%22,%23,%24,%25,%26,%27,%28,%29,%30,%31}, %32, %33, 1, 1, 1, 0, %34;"
    : "+f"(d[0]),"+f"(d[1]),"+f"(d[2]),"+f"(d[3]),"+f"(d[4]),"+f"(d[5]),"+f"(d[6]),"+f"(d[7]),"+f"(d[8]),"+f"(d[9]),"+f"(d[10]),"+f"(d[11]),"+f"(d[12]),"+f"(d[13]),"+f"(d[14]),"+f"(d[15]),"+f"(d[16]),"+f"(d[17]),"+f"(d[18]),"+f"(d[19]),"+f"(d[20]),"+f"(d[21]),"+f"(d[22]),"+f"(d[23]),"+f"(d[24]),"+f"(d[25]),"+f"(d[26]),"+f"(d[27]),"+f"(d[28]),"+f"(d[29]),"+f"(d[30]),"+f"(d[31])
    : "l"(da), "l"(db), "n"(TB));
}
template<int TB> __device__ __forceinline__ void wg_ss_n128(float* d, uint64_t da, uint64_t db) {
  asm volatile("wgmma.mma_async.sync.aligned.m64n128k16.f32.bf16.bf16 {%0,%1,%2,%3,%4,%5,%6,%7,%8,%9,%10,%11,%12,%13,%14,%15,%16,%17,%18,%19,%20,%21,%22,%23,%24,%25,%26,%27,%28,%29,%30,%31,%32,%33,%34,%35,%36,%37,%38,%39,%40,%41,%42,%43,%44,%45,%46,%47,%48,%49,%50,%51,%52,%53,%54,%55,%56,%57,%58,%59,%60,%61,%62,%63}, %64, %65, 1, 1, 1, 0, %66;"
    : "+f"(d[0]),"+f"(d[1]),"+f"(d[2]),"+f"(d[3]),"+f"(d[4]),"+f"(d[5]),"+f"(d[6]),"+f"(d[7]),"+f"(d[8]),"+f"(d[9]),"+f"(d[10]),"+f"(d[11]),"+f"(d[12]),"+f"(d[13]),"+f"(d[14]),"+f"(d[15]),"+f"(d[16]),"+f"(d[17]),"+f"(d[18]),"+f"(d[19]),"+f"(d[20]),"+f"(d[21]),"+f"(d[22]),"+f"(d[23]),"+f"(d[24]),"+f"(d[25]),"+f"(d[26]),"+f"(d[27]),"+f"(d[28]),"+f"(d[29]),"+f"(d[30]),"+f"(d[31]),"+f"(d[32]),"+f"(d[33]),"+f"(d[34]),"+f"(d[35]),"+f"(d[36]),"+f"(d[37]),"+f"(d[38]),"+f"(d[39]),"+f"(d[40]),"+f"(d[41]),"+f"(d[42]),"+f"(d[43]),"+f"(d[44]),"+f"(d[45]),"+f"(d[46]),"+f"(d[47]),"+f"(d[48]),"+f"(d[49]),"+f"(d[50]),"+f"(d[51]),"+f"(d[52]),"+f"(d[53]),"+f"(d[54]),"+f"(d[55]),"+f"(d[56]),"+f"(d[57]),"+f"(d[58]),"+f"(d[59]),"+f"(d[60]),"+f"(d[61]),"+f"(d[62]),"+f"(d[63])
    : "l"(da), "l"(db), "n"(TB));
}

__device__ __forceinline__ void wg_fence() { asm volatile("wgmma.fence.sync.aligned;" ::: "memory"); }
__device__ __forceinline__ void wg_commit() { asm volatile("wgmma.commit_group.sync.aligned;" ::: "memory"); }
template <int N> __device__ __forceinline__ void wg_wait() { asm volatile("wgmma.wait_group.sync.aligned %0;" ::"n"(N) : "memory"); }
template <int N> __device__ __forceinline__ void pin(float* r) {
#pragma unroll
  for (int i = 0; i < N; i++) asm volatile("" : "+f"(r[i])::"memory");
}
template <int N> __device__ __forceinline__ void clear(float* r) {
#pragma unroll
  for (int i = 0; i < N; i++) r[i] = 0.f;
  pin<N>(r);
}
template <int N> __device__ __forceinline__ void pin(uint32_t* r) {
#pragma unroll
  for (int i = 0; i < N; i++) asm volatile("" : "+r"(r[i])::"memory");
}
__device__ __forceinline__ constexpr uint64_t mkdesc(uint32_t addr, uint32_t lbo, uint32_t sbo, uint32_t swz) {
  return (uint64_t)((addr & 0x3FFFF) >> 4) | ((uint64_t)(lbo >> 4) << 16) | ((uint64_t)(sbo >> 4) << 32) | ((uint64_t)swz << 62);
}
__device__ __forceinline__ void mbar_init(uint32_t b, int c) { asm volatile("mbarrier.init.shared::cta.b64 [%0], %1;" ::"r"(b), "r"(c) : "memory"); }
__device__ __forceinline__ void mbar_expect(uint32_t b, int n) { asm volatile("mbarrier.arrive.expect_tx.shared::cta.b64 _, [%0], %1;" ::"r"(b), "r"(n) : "memory"); }
__device__ __forceinline__ void mbar_arrive(uint32_t b) { asm volatile("mbarrier.arrive.shared::cta.b64 _, [%0];" ::"r"(b) : "memory"); }
__device__ __forceinline__ bool mbar_try(uint32_t b, uint32_t ph) {
  uint32_t ok;
  asm volatile("{.reg .pred p; mbarrier.try_wait.parity.shared::cta.b64 p, [%1], %2; selp.u32 %0, 1, 0, p;}" : "=r"(ok) : "r"(b), "r"(ph) : "memory");
  return ok;
}
__device__ __forceinline__ void mbar_wait(uint32_t b, uint32_t ph) {
  if (mbar_try(b, ph)) return;
#pragma unroll 1
  for (int i = 0; i < (1 << 16); i++) {
    uint32_t ok;
    asm volatile("{.reg .pred p; mbarrier.try_wait.parity.shared::cta.b64 p, [%1], %2, 20000; selp.u32 %0, 1, 0, p;}" : "=r"(ok) : "r"(b), "r"(ph) : "memory");
    if (ok) return;
  }
  __trap();
}
__device__ __forceinline__ void bulk_load(uint32_t dst, const void* src, int bytes, uint32_t bar) {
  asm volatile("cp.async.bulk.shared::cluster.global.mbarrier::complete_tx::bytes [%0], [%1], %2, [%3];" ::"r"(dst), "l"(src), "r"(bytes), "r"(bar) : "memory");
}
__device__ __forceinline__ void tma_load(uint32_t dst, const CUtensorMap* m, int c0, int c1, uint32_t bar) {
  asm volatile("cp.async.bulk.tensor.2d.shared::cluster.global.mbarrier::complete_tx::bytes [%0], [%1, {%2, %3}], [%4];" ::"r"(dst), "l"(m), "r"(c0), "r"(c1), "r"(bar) : "memory");
}
__device__ __forceinline__ void tma_prefetch(const CUtensorMap* m, int c0, int c1) {
  asm volatile("cp.async.bulk.prefetch.tensor.2d.L2.global [%0, {%1, %2}];" ::"l"(m), "r"(c0), "r"(c1) : "memory");
}
__device__ __forceinline__ bool elect() {
  uint32_t r;
  asm volatile("{.reg .pred p; elect.sync _|p, 0xffffffff; selp.u32 %0, 1, 0, p;}" : "=r"(r));
  return r;
}
__device__ __forceinline__ void bar_sync(int id, int n) { asm volatile("bar.sync %0, %1;" ::"r"(id), "r"(n) : "memory"); }
__device__ __forceinline__ void bar_arrive(int id, int n) { asm volatile("bar.arrive %0, %1;" ::"r"(id), "r"(n) : "memory"); }
__device__ __forceinline__ bool bar_or(int id, int n, bool v) {
  uint32_t r;
  asm volatile("{.reg .pred p, q; setp.ne.u32 q, %3, 0; bar.red.or.pred p, %1, %2, q; selp.u32 %0, 1, 0, p;}" : "=r"(r) : "r"(id), "r"(n), "r"((uint32_t)v) : "memory");
  return r;
}
__device__ __forceinline__ void flag_add(int f) { asm volatile("red.release.gpu.global.add.u32 [%0], 1;" ::"l"(gFlag + f * 32) : "memory"); }
__device__ __forceinline__ void flag_wait(int f, uint32_t target, uint32_t ns) {
#pragma unroll 1
  for (int i = 0; i < (1 << 22); i++) {
    uint32_t v;
    asm volatile("ld.acquire.gpu.global.u32 %0, [%1];" : "=r"(v) : "l"(gFlag + f * 32) : "memory");
    if ((int)(v - target) >= 0) { asm volatile("fence.proxy.async.global;" ::: "memory"); return; }
    __nanosleep(ns);
  }
  __trap();
}
__device__ __forceinline__ float ex2(float x) { float y; asm("ex2.approx.ftz.f32 %0, %1;" : "=f"(y) : "f"(x)); return y; }
__device__ __forceinline__ float rcp(float x) { float y; asm("rcp.approx.ftz.f32 %0, %1;" : "=f"(y) : "f"(x)); return y; }
__device__ __forceinline__ uint32_t packbf(float lo, float hi) { uint32_t d; asm("cvt.rn.bf16x2.f32 %0, %1, %2;" : "=r"(d) : "f"(hi), "f"(lo)); return d; }
__device__ __forceinline__ float bfr(float x) { return __bfloat162float(__float2bfloat16(x)); }
__device__ __forceinline__ uint32_t hmul(uint32_t a, uint32_t b) { uint32_t d; asm("mul.rn.bf16x2 %0, %1, %2;" : "=r"(d) : "r"(a), "r"(b)); return d; }
__device__ __forceinline__ uint32_t hadd(uint32_t a, uint32_t b) { uint32_t d; asm("add.rn.bf16x2 %0, %1, %2;" : "=r"(d) : "r"(a), "r"(b)); return d; }
__device__ __forceinline__ uint32_t hsub(uint32_t a, uint32_t b) { uint32_t d; asm("sub.rn.bf16x2 %0, %1, %2;" : "=r"(d) : "r"(a), "r"(b)); return d; }
__device__ __forceinline__ void hmma(float* c, const uint4& a, uint32_t b0, uint32_t b1) {
  asm("mma.sync.aligned.m16n8k16.row.col.f32.bf16.bf16.f32 {%0,%1,%2,%3},{%4,%5,%6,%7},{%8,%9},{%0,%1,%2,%3};"
      : "+f"(c[0]), "+f"(c[1]), "+f"(c[2]), "+f"(c[3]) : "r"(a.x), "r"(a.y), "r"(a.z), "r"(a.w), "r"(b0), "r"(b1));
}
constexpr float LOG2E = 1.4426950408889634f;

__device__ __forceinline__ uint32_t exp_poly(float lo, float hi, uint32_t half2) {
  uint32_t u, mh, p;
  asm("cvt.pack.sat.s16.s32 %0, %1, %2;" : "=r"(u) : "r"(__float_as_uint(hi)), "r"(__float_as_uint(lo)));
  asm("lop3.b32 %0, %1, 0x007F007F, %2, 0xEA;" : "=r"(mh) : "r"(u), "r"(half2));
  asm("fma.rn.bf16x2 %0, %1, %2, %3;" : "=r"(p) : "r"(u), "r"(mh), "r"(u & 0xFF80FF80u));
  return p;
}
__device__ __forceinline__ void softmax64(float* s, uint32_t* p, uint32_t half2) {
  pin<32>(s);
#pragma unroll
  for (int j = 0; j < 8; j++) {
#pragma unroll
    for (int r = 0; r < 2; r++) {
      const float a = s[4 * j + 2 * r], b = s[4 * j + 2 * r + 1];
      p[2 * j + r] = ((POLYMASK >> j) & 1) ? exp_poly(a, b, half2) : packbf(ex2(a), ex2(b));
    }
  }
  pin<16>(p);
}

__device__ __forceinline__ void tile_max(float* s, float* m) {
  pin<32>(s);
#pragma unroll
  for (int j = 0; j < 8; j++) {
    float* mm = m + (((POLYMASK >> j) & 1) ? 0 : 2);
    mm[0] = fmaxf(mm[0], fmaxf(s[4 * j], s[4 * j + 1]));
    mm[1] = fmaxf(mm[1], fmaxf(s[4 * j + 2], s[4 * j + 3]));
  }
}
__device__ __forceinline__ float shift_of(float mpoly, float mmufu) {
  float v = fmaxf(mmufu, (mpoly * 0x1p71f) * 0x1p71f);
  v = fmaxf(v, __shfl_xor_sync(~0u, v, 1));
  v = fmaxf(v, __shfl_xor_sync(~0u, v, 2));
  return __fadd_rn(__fadd_rn(12582976.f, -v), -12582912.f);
}
__device__ __forceinline__ uint32_t shift_frag(float shift, int t) {
  const float y = shift * 0x1p-71f;
  const float r1 = y - __uint_as_float(__float_as_uint(y) & 0xFFFF0000u);
  const float r2 = r1 - __uint_as_float(__float_as_uint(r1) & 0xFFFF0000u);
  const uint32_t w0 = __byte_perm(__float_as_uint(y), __float_as_uint(r1), 0x7632), w1 = __byte_perm(__float_as_uint(r2), 0x1C000000u, 0x7632);
  const uint32_t lo = t == 0 ? w0 : w1, hi = t == 2 ? 0x1C00u : 0u;
  return t < 2 ? lo : hi;
}

struct Tile { int kind, c0, c1; };
__device__ __forceinline__ Tile tile_of(int cg, int t) {
  const int c2 = cg >> 1;
  Tile r;
  if (cg & 1) {
    if (t == 0) { r.kind = 1; r.c0 = c2 * 128; r.c1 = r.c0 + 64; }
    else { r.kind = 2; r.c0 = r.c1 = (7 * c2 + 2 + t) * 64; }
  } else {
    if (t < 2) { r.kind = 0; r.c0 = 512 + c2 * 128 + t * 64; r.c1 = r.c0 + 512; }
    else { r.kind = 2; r.c0 = r.c1 = (7 * c2 + t - 2) * 64; }
  }
  return r;
}

__global__ void __launch_bounds__(NTHREADS, 1)
fused_kernel(const __grid_constant__ CUtensorMap mQKV, const __grid_constant__ CUtensorMap mW1, const __grid_constant__ CUtensorMap mW3,
             const __grid_constant__ CUtensorMap mW2, const __grid_constant__ CUtensorMap mWO, const __grid_constant__ CUtensorMap mX,
             const bf16* __restrict__ x, bf16* __restrict__ out,
             uint32_t zero) {
  extern __shared__ __align__(1024) uint8_t smem[];
  constexpr uint32_t sb = 1024;
  if ((uint32_t)__cvta_generic_to_shared(smem) != sb) __trap();
  const int tid = threadIdx.x, lane = tid & 31, g = lane >> 2, t = lane & 3;
  const int warp = __shfl_sync(~0u, tid >> 5, 0), wg = warp >> 2, w = warp & 3;
  const int b = blockIdx.x;
  const int rb = b >> 3, cg = b & 7;
  const int head = b & 31, qb = b >> 5;
  const int rEarly = (rb >> 2) * 8 + ((0x3052 >> ((rb & 3) * 4)) & 7), rLate = (rb >> 2) * 8 + ((0x6741 >> ((rb & 3) * 4)) & 7);

  if (warp == 0) {
    if (elect()) {
#pragma unroll
      for (int j = 0; j < 8; j++) mbar_init(sb + B_KV + 8 * j, 1);
      asm volatile("fence.mbarrier_init.release.cluster;" ::: "memory");
#pragma unroll
      for (int j = 0; j < 8; j++) {
        mbar_expect(sb + B_KV + 8 * j, 16384);
        tma_load(sb + SM_A + j * 16384, &mX, j * 64, rb * 128, sb + B_KV + 8 * j);
      }
    }
    __syncwarp();
  }
  if (wg == 4) {
    asm volatile("setmaxnreg.dec.sync.aligned.u32 24;");
    if (w == 0) {
      TSTAMP(2, 6);
      if (elect()) {
#pragma unroll
        for (int i = 0; i < 2 * NSLOT; i++) mbar_init(sb + B_FULL1 + 8 * i, 1);
#pragma unroll
        for (int i = 0; i < NSLOT; i++) mbar_init(sb + B_EMPTY1 + 8 * i, 8);
#pragma unroll
        for (int i = 8; i < 26; i++) mbar_init(sb + B_KV + 8 * i, i < 18 ? 1 : i < 23 ? 4 : i == 23 ? 12 : i == 24 ? 1 : 8);
        asm volatile("fence.mbarrier_init.release.cluster;" ::: "memory");
      }
      __syncwarp();
      bar_arrive(1, 544);
      uint32_t epoch = 0;
      TSTAMP(2, 7);
      int slot = 0;
      uint32_t ph = 1;
#pragma unroll 1
      for (int tI = 0; tI < 5; tI++) {
        const Tile tl = tile_of(cg, tI);
        const CUtensorMap *m0 = tl.kind == 2 ? &mW1 : &mQKV, *m1 = tl.kind == 2 ? &mW3 : &mQKV;
#pragma unroll 1
        for (int k = 0; k < 8; k++) {
          const uint32_t full = sb + B_FULL1 + 8 * ((tI & 1) * NSLOT + slot), dst = sb + SM_RING + slot * 16384;
          if (tI == 4 && k == 0) {
            epoch = (epoch >> 5) + 1;
            flag_wait(F_QKV + (head >> 2), epoch * 32, 32);
            if (elect()) {
              mbar_expect(sb + B_K0, 2048);
              bulk_load(sb + SM_MERGE, gKV + (size_t)head * 131072, 2048, sb + B_K0);
            }
          }
          if (tI == 0 && k == NSLOT) {
            asm volatile("ld.relaxed.gpu.global.u32 %0, [%1];" : "=r"(epoch) : "l"(gFlag + F_O * 32) : "memory");
            const int i = 2 * NSLOT + rb + lane * 16;
            if (i < 80) {
              const Tile tp = tile_of(cg, i >> 4);
              tma_prefetch((i & 1) ? (tp.kind == 2 ? &mW3 : &mQKV) : (tp.kind == 2 ? &mW1 : &mQKV), (i & 1) ? tp.c1 : tp.c0, ((i >> 1) & 7) * 64);
            }
            __syncwarp();
          }
          mbar_wait(sb + B_EMPTY1 + 8 * slot, ph);
          if (elect()) {
            mbar_expect(full, 16384);
            tma_load(dst, m0, tl.c0, k * 64, full);
            tma_load(dst + 8192, m1, tl.c1, k * 64, full);
          }
          if (++slot == NSLOT) { slot = 0; ph ^= 1; }
        }
      }
#pragma unroll 1
      for (int j = 0; j < 8; j++) {
        if (j >= 8 - NSLOT) {
          mbar_wait(sb + B_EMPTY1 + 8 * slot, ph);
          if (++slot == NSLOT) { slot = 0; ph ^= 1; }
        }
        if (elect()) {
          mbar_expect(sb + B_KV + 8 * j, 16384);
          bulk_load(sb + SM_A + j * 16384, gKV + (size_t)head * 131072 + j * 16384, 16384, sb + B_KV + 8 * j);
        }
      }
      flag_wait(F_H + rEarly, epoch * 28, 100);
      flag_wait(F_H + rLate, epoch * 28, 100);
      slot = 0; ph = 1;
#pragma unroll 1
      for (int n = 0; n < 31; n++) {
        const uint32_t full = sb + B_FULL2 + 8 * slot, dst = sb + SM_RING + slot * 24576;
        mbar_wait(sb + B_EMPTY2 + 8 * slot, ph);
        if (n < 28 && elect()) {
          mbar_expect(full, 24576);
          tma_load(dst, &mW2, cg * 64, n * 64, full);
          bulk_load(dst + 8192, gH + (size_t)(rEarly * 28 + n) * 8192, 8192, full);
          bulk_load(dst + 16384, gH + (size_t)(rLate * 28 + n) * 8192, 8192, full);
        }
        if (++slot == 3) { slot = 0; ph ^= 1; }
      }
      if (elect()) {
        mbar_expect(sb + B_WO, 65536);
#pragma unroll 1
        for (int k = 0; k < 8; k++) tma_load(sb + SM_RING + k * 8192, &mWO, cg * 64, k * 64, sb + B_WO);
      }
      flag_wait(F_O + rEarly, epoch * 32, 200);
#pragma unroll 1
      for (int n = 0; n < 8; n++) {
        mbar_wait(sb + B_OEE + 8 * (n & 1), ((n >> 1) & 1) ^ 1);
        if (elect()) {
          mbar_expect(sb + B_OE + 8 * (n & 1), 8192);
          bulk_load(sb + SM_RING + 65536 + (n & 1) * 8192, gO + (size_t)(rEarly * 8 + n) * 8192, 8192, sb + B_OE + 8 * (n & 1));
        }
      }
      mbar_wait(sb + B_ADONE, 0);
      flag_wait(F_O + rLate, epoch * 32, 20);
      if (elect()) {
#pragma unroll
        for (int i = 0; i < 4; i++) {
          mbar_expect(sb + B_O + 8 * i, 16384);
          bulk_load(sb + SM_A + i * 16384, gO + (size_t)rLate * 65536 + i * 16384, 16384, sb + B_O + 8 * i);
        }
      }
    } else {
      if (w < 3) {
#pragma unroll 1
        for (int tI = w - 1; tI < 5; tI += 2) {
          const Tile tl = tile_of(cg, tI);
          bar_sync(3 + w, 288);
          if (lane < (tl.kind ? 2 : 1)) flag_add(tl.kind == 2 ? F_H + rb * 2 + lane : F_QKV + ((tl.c0 >> 6) & 7) + lane);
          __syncwarp();
        }
      }
#pragma unroll 1
      for (int i = 0; i < (w == 2 ? 2 : 3); i++) {
        bar_sync(12 + w, 160);
        if (lane == 0) flag_add(F_O + qb * 8 + (((w == 1 ? 0x102 : w == 2 ? 0x43 : 0x765) >> (i * 4)) & 7));
        __syncwarp();
      }
    }
    return;
  }

  TSTAMP(wg, 0);
  asm volatile("setmaxnreg.inc.sync.aligned.u32 112;");

  {
    if (tid < 128) ((uint32_t*)(smem + SM_ONES))[tid] = 0x3F803F80u;
    {
      const int n = tid >> 3, k = (tid & 7) * 2;
      const bool poly = (POLYMASK >> (n >> 3)) & 1;
      const float cm = -127.f + 0.5849625f - 0.0020f, chi = bfr(cm), clo = cm - chi, sc = poly ? 0x1p-71f : 0x1p71f;
      float v0 = 0.f, v1 = 0.f;
      if (k == 0) { v0 = sc; v1 = sc; }
      if (k == 2) { v0 = sc; v1 = poly ? 0.f : chi * sc; }
      if (k == 4) { v0 = poly ? 0.f : clo * sc; }
      *(uint32_t*)(smem + SM_BIAS + n * 32 + (((k >> 3) ^ ((n >> 2) & 1)) << 4) + (k & 7) * 2) = packbf(v0, v1);
    }
    float cs[4] = {0.f, 0.f, 0.f, 0.f}, ca[4] = {0.f, 0.f, 0.f, 0.f}, cb[4] = {0.f, 0.f, 0.f, 0.f};
    uint4 xv[16];
    const int row = warp * 8 + g;
    uint8_t* xs = smem + SM_A + row * 128;
    const int xo0 = (((4 * (g & 1) + t) ^ g) << 4), xo1 = xo0 ^ 64;
    bar_sync(2, 512);
#pragma unroll
    for (int j = 0; j < 16; j++) {
      if ((j & 1) == 0) mbar_wait(sb + B_KV + 4 * j, 0);
      if (j == 0 && wg == 3) TSTAMP(3, 7);
      if (j == 8 && wg == 3) TSTAMP(3, 13);
      if (j == 14 && wg == 3) TSTAMP(3, 14);
      xv[j] = *(const uint4*)(xs + (j >> 1) * 16384 + ((j & 1) ? xo1 : xo0));
      hmma(cs, xv[j], 0x3F803F80u, 0x3F803F80u);
      hmma(ca, xv[j], xv[j].x, xv[j].z);
      hmma(cb, xv[j], xv[j].y, xv[j].w);
    }
    const float mean = (cs[0] + cs[2]) * (1.f / DM);
    const uint32_t m2 = packbf(mean, mean);
    if (m2 != 0x12345678) TSTAMP(4, wg);
#pragma unroll
    for (int j = 0; j < 16; j++)
      *(uint4*)(xs + (j >> 1) * 16384 + ((j & 1) ? xo1 : xo0)) = make_uint4(hsub(xv[j].x, m2), hsub(xv[j].y, m2), hsub(xv[j].z, m2), hsub(xv[j].w, m2));
    {
      const float var = fmaxf(((g & 1) ? ca[1] + cb[3] : ca[0] + cb[2]) * (1.f / DM) - mean * mean, 0.f);
      float sd;
      asm("sqrt.approx.f32 %0, %1;" : "=f"(sd) : "f"(bfr(bfr(var) + 1e-5f)));
      if (t == (g >> 1)) ((float*)(smem + SM_RSTD))[row] = rcp(bfr(sd));
    }
    TSTAMP(4, 4 + wg);
    asm volatile("fence.proxy.async.shared::cta;" ::: "memory");
    bar_sync(1, 544);
  }
  TSTAMP(wg, 1);
  const int pair = wg >> 1, half = wg & 1;

  {
    uint32_t par = 0;
    const uint64_t dA0 = mkdesc(sb + SM_A + half * 8192, 16, 1024, 1), dB0 = mkdesc(sb + SM_RING, 8192, 1024, 1);
#pragma unroll 1
    for (int tI = pair; tI < 5; tI += 2) {
      float acc[64];
      clear<64>(acc);
      int slot = (tI * 8) % NSLOT, prev = 0;
#pragma unroll 1
      for (int k = 0; k < 8; k++) {
        mbar_wait(sb + B_FULL1 + 8 * (pair * NSLOT + slot), (par >> slot) & 1);
        par ^= 1u << slot;
        if (tI == 0 && wg == 0) TSTAMP(4, 8 + k);
        const uint64_t dA = dA0 + k * 1024, dB = dB0 + slot * 1024;
        wg_fence();
        wg_ss_n128<1>(acc, dA, dB);
        wg_ss_n128<1>(acc, dA + 2, dB + 128);
        wg_ss_n128<1>(acc, dA + 4, dB + 256);
        wg_ss_n128<1>(acc, dA + 6, dB + 384);
        wg_commit();
        if (k > 0) {
          wg_wait<1>();
          if (lane == 0) mbar_arrive(sb + B_EMPTY1 + 8 * prev);
        }
        prev = slot;
        if (++slot == NSLOT) slot = 0;
      }
      wg_wait<0>();
      if (lane == 0) mbar_arrive(sb + B_EMPTY1 + 8 * prev);
      pin<64>(acc);
      TSTAMP(wg, 2 + (tI >> 1) * 2);
      const Tile tl = tile_of(cg, tI);
      const int lrow = half * 64 + w * 16 + g;
      const float r0 = ((const float*)(smem + SM_RSTD))[lrow], r1 = ((const float*)(smem + SM_RSTD))[lrow + 8];
      if (tl.kind == 2) {
        uint32_t* hp = (uint32_t*)(gH + (size_t)((rb * 2 + half) * 28 + (tl.c0 >> 6)) * 8192 + w * 256) + lane;
#pragma unroll
        for (int j = 0; j < 8; j++) {
#pragma unroll
          for (int r = 0; r < 2; r++) {
            const float rs = r ? r1 : r0, e = -LOG2E * rs, q = rs * rs;
            const float g0 = acc[4 * j + 2 * r], g1 = acc[4 * j + 2 * r + 1];
            const float h0 = (g0 * q) * acc[32 + 4 * j + 2 * r] * rcp(1.f + ex2(g0 * e));
            const float h1 = (g1 * q) * acc[33 + 4 * j + 2 * r] * rcp(1.f + ex2(g1 * e));
            hp[j * 256 + r * 32] = packbf(h0, h1);
          }
        }
      } else {
        const int hg = (tl.c0 >> 6) & 7;
#pragma unroll
        for (int u = 0; u < 2; u++) {
#pragma unroll
          for (int r = 0; r < 2; r++) {
            float sc = r ? r1 : r0;
            uint8_t* p;
            size_t hs;
            if (tl.kind == 1) {
              sc *= 0.25f * LOG2E * 0x1p-71f;
              p = gQ + (size_t)(hg + u) * 4 * 65536 + (size_t)(rb * 128 + lrow + r * 8) * 32 + t * 8;
              hs = 65536;
            } else {
              if (u == 0) sc *= ((POLYMASK >> (2 * w + r)) & 1) ? 0x1p-71f : 0x1p71f;
              p = gKV + (size_t)hg * 4 * 131072 + rb * 8192 + u * 4096 + (lrow + r * 8) * 32 + ((t * 8) ^ ((g & 4) << 2));
              hs = 131072;
            }
#pragma unroll
            for (int hh = 0; hh < 4; hh++) {
              const float* a = acc + u * 32 + hh * 8 + 2 * r;
              *(uint2*)(p + hh * hs) = make_uint2(packbf(a[0] * sc, a[1] * sc), packbf(a[4] * sc, a[5] * sc));
            }
          }
        }
      }
      bar_arrive(4 + pair, 288);
      TSTAMP(wg, 3 + (tI >> 1) * 2);
    }
  }

  const uint8_t* qbase = gQ + (size_t)head * 65536 + (size_t)(qb * 512 + w * 16 + g) * 32 + t * 4;
  auto load_q = [&](uint32_t* q, int rbl) {
    const uint32_t* qp = (const uint32_t*)(qbase + rbl * 2048);
    q[0] = __ldcg(qp); q[1] = __ldcg(qp + 64); q[2] = __ldcg(qp + 4); q[3] = __ldcg(qp + 68);
  };
  if (pair == 1) {
    mbar_wait(sb + B_K0, 0);
    uint32_t q4[16];
#pragma unroll
    for (int i = 0; i < 4; i++) load_q(q4 + 4 * i, half * 4 + i);
    const uint64_t dK0 = mkdesc(sb + SM_MERGE, 16, 256, 3);
#pragma unroll
    for (int i = 0; i < 4; i += 2) {
      float s[64];
      wg_fence();
      wg_rs_n64<0, 0>(s, q4 + 4 * i, dK0);
      wg_rs_n64<0, 0>(s + 32, q4 + 4 * i + 4, dK0);
      wg_commit();
      wg_wait<0>();
#pragma unroll
      for (int j = 0; j < 2; j++) {
        float m[4] = {-INFINITY, -INFINITY, -INFINITY, -INFINITY};
        tile_max(s + 32 * j, m);
        const float s0 = shift_of(m[0], m[2]), s1 = shift_of(m[1], m[3]);
        if (t < 2) ((float*)(smem + SM_SHIFT))[(half * 4 + i + j) * 64 + w * 16 + t * 8 + g] = t ? s1 : s0;
      }
    }
    __syncwarp();
    if (lane == 0) mbar_arrive(sb + B_SHIFT);
  }

  if (wg < 3) {
    asm volatile("setmaxnreg.inc.sync.aligned.u32 120;");
    constexpr uint64_t VS = (uint64_t)(32 - (32LL << 16));
    const uint32_t half2 = 0x3F003F00u + zero;
    const uint64_t dBias = mkdesc(sb + SM_BIAS, 16, 256, 3);
    const uint64_t dV0 = mkdesc(sb + SM_A + 4096, SM_ONES - SM_A - 4096, 256, 3);
    const float* shifts = (const float*)(smem + SM_SHIFT) + w * 16 + g;
#define SEG(r, c0, cl, mode) (uint64_t)((r) | (c0) << 3 | (cl) << 7 | (mode) << 11 | 1 << 13)
    uint64_t segs = wg == 0   ? SEG(2, 5, 15, 2) | SEG(0, 0, 15, 0) << 16 | SEG(1, 0, 15, 0) << 32
                    : wg == 1 ? SEG(2, 0, 4, 1) | SEG(5, 11, 15, 1) << 16 | SEG(3, 0, 15, 0) << 32 | SEG(4, 0, 15, 0) << 48
                              : SEG(5, 0, 10, 2) | SEG(6, 0, 15, 0) << 16 | SEG(7, 0, 15, 0) << 32;
    uint32_t q[4], qa[4], p0[16], p1[16];
    float s[32], o[12], shift[2];
    clear<32>(s);
    int ready = wg == 0 ? 2 : 0;
    mbar_wait(sb + B_SHIFT, 0);
    load_q(q, segs & 7);
    shift[0] = shifts[(segs & 7) * 64];
    shift[1] = shifts[(segs & 7) * 64 + 8];
    qa[2] = zero & q[0];
    qa[3] = zero & q[1];
    mbar_wait(sb + B_KV + 8 * ready, 1);
    TSTAMP(wg, 8);
    bool exact = false;
    bool primed = false;
#pragma unroll 1
    while (true) {
      const uint32_t sg = (uint32_t)segs, sn = sg >> 16;
      const int rbl = sg & 7, c0 = (sg >> 3) & 15, cl = (sg >> 7) & 15, mode = (sg >> 11) & 3;
      uint64_t c = dV0 + (uint64_t)c0 * (16 * VS);
      if (!primed) {
        if (exact) {
          load_q(q, rbl);
          float m[4] = {-INFINITY, -INFINITY, -INFINITY, -INFINITY};
#pragma unroll 1
          for (int i = 2 * c0; i < 2 * cl + 2; i++) {
            wg_fence();
            wg_rs_n64<0, 2>(s, q, dV0 - 256 + (i >> 1) * 512 + (i & 1) * 128);
            wg_commit();
            wg_wait<0>();
            tile_max(s, m);
          }
          shift[0] = shift_of(m[0], m[2]);
          shift[1] = shift_of(m[1], m[3]);
        }
        qa[0] = shift_frag(shift[0], t);
        qa[1] = shift_frag(shift[1], t);
        wg_fence();
        wg_rs_n64<0, 2>(s, qa, dBias);
        wg_rs_n64<0, 1>(s, q, c - 256);
        wg_commit();
        wg_wait<0>();
      }
      uint32_t qn[4];
      load_q(qn, sn & 7);
      clear<12>(o);
      auto first_half = [&]() {
        softmax64(s, p0, half2);
        wg_fence();
        wg_rs_n64<0, 2>(s, qa, dBias);
        wg_rs_n64<0, 1>(s, q, c - 128);
        wg_commit();
#pragma unroll
        for (int k = 0; k < 4; k++) wg_rs_n24<1, 1>(o, p0 + 4 * k, c + k * VS);
        wg_commit();
        wg_wait<1>();
        softmax64(s, p1, half2);
      };
      auto second_half = [&](uint64_t dKnext) {
        wg_fence();
        wg_rs_n64<0, 2>(s, qa, dBias);
        wg_rs_n64<0, 1>(s, q, dKnext);
        wg_commit();
#pragma unroll
        for (int k = 0; k < 4; k++) wg_rs_n24<1, 1>(o, p1 + 4 * k, c + (4 + k) * VS);
        wg_commit();
      };
#pragma unroll 1
      for (int ci = c0; ci < cl;) {
        if (ready < 7) mbar_wait(sb + B_KV + 8 * ++ready, 1);
        ci = ready >= 7 ? cl : min(cl, 2 * ready);
        const uint32_t cend = (uint32_t)dV0 + ci * (uint32_t)(16 * VS);
#pragma unroll 1
        do {
          first_half();
          second_half(c + 256);
          c += 16 * VS;
          wg_wait<1>();
        } while ((uint32_t)c != cend);
      }
      if (ready < 8) {
#pragma unroll 1
        for (int j = 0; j < 8; j++) mbar_wait(sb + B_KV + 8 * j, 1);
        ready = 8;
      }
      const float bias[2] = {shift[0], shift[1]};
      shift[0] = shifts[(sn & 7) * 64];
      shift[1] = shifts[(sn & 7) * 64 + 8];
      first_half();
      qa[0] = shift_frag(shift[0], t);
      qa[1] = shift_frag(shift[1], t);
#pragma unroll
      for (int i = 0; i < 4; i++) q[i] = qn[i];
      pin<4>(q);
      pin<2>(qa);
      second_half(dV0 - 256 + ((sn >> 3) & 15) * 512);
      wg_wait<0>();
      pin<12>(o);
      exact = __all_sync(~0u, bar_or(10 + wg, 128, !exact && !(o[8] < 0x1p90f && o[10] < 0x1p90f)));
      primed = !exact;
      if (exact) continue;
      segs >>= 16;
      if (mode == 1) {
        float* mp = (float*)(smem + SM_MERGE + (rbl >> 2) * 6144) + (tid & 127);
        o[9] = bias[0]; o[11] = bias[1];
#pragma unroll
        for (int i = 0; i < 12; i++) mp[i * 128] = o[i];
        bar_arrive(8 + (rbl >> 2), 256);
        continue;
      }
      if (mode == 2) {
        const float* mp = (const float*)(smem + SM_MERGE + (wg >> 1) * 6144) + (tid & 127);
        bar_sync(8 + (wg >> 1), 256);
#pragma unroll
        for (int r = 0; r < 2; r++) {
          const float bo = mp[(9 + 2 * r) * 128], bm = fminf(bo, bias[r]);
          const float fa = ex2(0.5f * (bm - bias[r])), fb = ex2(0.5f * (bm - bo));
          o[2 * r] = o[2 * r] * fa * fa + mp[(2 * r) * 128] * fb * fb;
          o[2 * r + 1] = o[2 * r + 1] * fa * fa + mp[(2 * r + 1) * 128] * fb * fb;
          o[4 + 2 * r] = o[4 + 2 * r] * fa * fa + mp[(4 + 2 * r) * 128] * fb * fb;
          o[5 + 2 * r] = o[5 + 2 * r] * fa * fa + mp[(5 + 2 * r) * 128] * fb * fb;
          o[8 + 2 * r] = o[8 + 2 * r] * fa * fa + mp[(8 + 2 * r) * 128] * fb * fb;
        }
      }
      if (sn == 0 && lane == 0) mbar_arrive(sb + B_ADONE);
#pragma unroll
      for (int r = 0; r < 2; r++) {
        const float inv = rcp(o[8 + 2 * r]);
        const uint32_t a = packbf(o[2 * r] * inv, o[2 * r + 1] * inv), d = packbf(o[4 + 2 * r] * inv, o[5 + 2 * r] * inv);
        const uint32_t e = __shfl_xor_sync(~0u, (t & 2) ? a : d, 2);
        *(uint2*)(gO + (size_t)((qb * 8 + rbl) * 8 + (head >> 2)) * 8192 + ((head & 3) * 2 + (t & 1)) * 1024 + (2 * w + r) * 128 + g * 16 + (t & 2) * 4) =
            (t & 2) ? make_uint2(e, d) : make_uint2(a, e);
      }
      bar_arrive(13 + wg, 160);
      TSTAMP(wg, sn == 0 ? 11 : mode ? 9 : 10);
      if (sn == 0) break;
    }
  } else {
    asm volatile("setmaxnreg.dec.sync.aligned.u32 96;");
    uint32_t gate[32];
    const uint64_t dB0 = mkdesc(sb + SM_RING, 8192, 1024, 1);
    {
      const uint64_t dA0 = mkdesc(sb + SM_RING + 8192, 1024, 128, 0);
      float acc[64];
      clear<64>(acc);
      int slot = 0;
      uint32_t ph = 0;
#pragma unroll 1
      for (int n = 0; n < 28; n++) {
        mbar_wait(sb + B_FULL2 + 8 * slot, ph);
        const uint64_t dA = dA0 + slot * 1536, dB = dB0 + slot * 1536;
        wg_fence();
#pragma unroll
        for (int k = 0; k < 4; k++) {
          wg_ss_n64<1>(acc, dA + k * 128, dB + k * 128);
          wg_ss_n64<1>(acc + 32, dA + 512 + k * 128, dB + k * 128);
        }
        wg_commit();
        wg_wait<0>();
        if (lane == 0) mbar_arrive(sb + B_EMPTY2 + 8 * slot);
        if (++slot == 3) { slot = 0; ph ^= 1; }
      }
      pin<64>(acc);
#pragma unroll
      for (int i = 0; i < 32; i++) {
        const uint32_t f = packbf(acc[2 * i], acc[2 * i + 1]);
        const float f0 = __uint_as_float(f << 16), f1 = __uint_as_float(f & 0xFFFF0000u);
        gate[i] = packbf(f0 * rcp(1.f + ex2(-LOG2E * f0)), f1 * rcp(1.f + ex2(-LOG2E * f1)));
      }
      mbar_wait(sb + B_WO, 0);
    }
    TSTAMP(wg, 8);
#pragma unroll
    for (int pass = 0; pass < 2; pass++) {
      const size_t off = (size_t)((pass ? rLate : rEarly) * 64 + w * 16 + g) * DM + cg * 64 + (t & 1) * 8 + (t & 2) * 2;
      uint2 xr[8];
#pragma unroll
      for (int i = 0; i < 8; i++) xr[i] = __ldg((const uint2*)(x + off + (i & 1) * 8 * DM + (i >> 1) * 16));
      float acc[32];
      clear<32>(acc);
      if (pass == 0) {
        const uint64_t dA0 = mkdesc(sb + SM_RING + 65536, 1024, 128, 0);
#pragma unroll 1
        for (int n = 0; n < 8; n++) {
          mbar_wait(sb + B_OE + 8 * (n & 1), (n >> 1) & 1);
          wg_fence();
#pragma unroll
          for (int k = 0; k < 4; k++) wg_ss_n64<1>(acc, dA0 + (n & 1) * 512 + k * 128, dB0 + n * 512 + k * 128);
          wg_commit();
          wg_wait<0>();
          if (lane == 0) mbar_arrive(sb + B_OEE + 8 * (n & 1));
        }
      } else {
        mbar_wait(sb + B_ADONE, 0);
        const uint64_t dA = mkdesc(sb + SM_A, 1024, 128, 0);
#pragma unroll 1
        for (int n = 0; n < 4; n++) {
          mbar_wait(sb + B_O + 8 * n, 0);
          wg_fence();
#pragma unroll
          for (int k = 0; k < 8; k++) wg_ss_n64<1>(acc, dA + (n * 8 + k) * 128, dB0 + (n * 8 + k) * 128);
          wg_commit();
        }
        wg_wait<0>();
      }
      pin<32>(acc);
      TSTAMP(wg, 9 + 2 * pass);
#pragma unroll
      for (int i = 0; i < 8; i++) {
        const int ia = (i >> 1) * 4 + (i & 1), ib = ia + 2;
        const uint32_t ya = hmul(packbf(acc[2 * ia], acc[2 * ia + 1]), gate[pass * 16 + ia]);
        const uint32_t yb = hmul(packbf(acc[2 * ib], acc[2 * ib + 1]), gate[pass * 16 + ib]);
        const uint32_t e = __shfl_xor_sync(~0u, (t & 1) ? ya : yb, 1);
        const uint32_t lo = (t & 1) ? e : ya, hi = (t & 1) ? yb : e;
        *(uint2*)(out + off + (i & 1) * 8 * DM + (i >> 1) * 16) = make_uint2(hadd(xr[i].x, lo), hadd(xr[i].y, hi));
      }
      TSTAMP(wg, 10 + 2 * pass);
    }
  }
}

typedef CUresult (*EncodeFn)(CUtensorMap*, CUtensorMapDataType, cuuint32_t, void*, const cuuint64_t*, const cuuint64_t*, const cuuint32_t*,
                             const cuuint32_t*, CUtensorMapInterleave, CUtensorMapSwizzle, CUtensorMapL2promotion, CUtensorMapFloatOOBfill);

void make_map(EncodeFn enc, CUtensorMap* m, void* p, int rows, int cols, int boxrows = 64) {
  const cuuint64_t dims[2] = {(cuuint64_t)cols, (cuuint64_t)rows}, strides[1] = {(cuuint64_t)cols * 2};
  const cuuint32_t box[2] = {64, (cuuint32_t)boxrows}, es[2] = {1, 1};
  enc(m, CU_TENSOR_MAP_DATA_TYPE_BFLOAT16, 2, p, dims, strides, box, es, CU_TENSOR_MAP_INTERLEAVE_NONE, CU_TENSOR_MAP_SWIZZLE_128B,
      CU_TENSOR_MAP_L2_PROMOTION_L2_128B, CU_TENSOR_MAP_FLOAT_OOB_FILL_NONE);
}

}

extern "C" void kernel_launch(void* const* d_in, const int* in_sizes, int n_in, void* d_out, int out_size) {
  (void)in_sizes; (void)n_in; (void)out_size;
  void* fn = nullptr;
  cudaDriverEntryPointQueryResult qr;
  cudaGetDriverEntryPoint("cuTensorMapEncodeTiled", &fn, cudaEnableDefault, &qr);
  EncodeFn enc = (EncodeFn)fn;
  CUtensorMap mQKV, mW1, mW3, mW2, mWO, mX;
  make_map(enc, &mX, d_in[0], SEQ, DM, 128);
  make_map(enc, &mQKV, d_in[1], DM, 3 * DM);
  make_map(enc, &mWO, d_in[2], DM, DM);
  make_map(enc, &mW1, d_in[4], DM, FF);
  make_map(enc, &mW3, d_in[5], DM, FF);
  make_map(enc, &mW2, d_in[6], FF, DM);
  cudaFuncSetAttribute(fused_kernel, cudaFuncAttributeMaxDynamicSharedMemorySize, SM_TOTAL);
  fused_kernel<<<128, NTHREADS, SM_TOTAL>>>(mQKV, mW1, mW3, mW2, mWO, mX, (const bf16*)d_in[0], (bf16*)d_out, 0u);
}
```

```cpp
#include <cuda_runtime.h>
#include <cuda_bf16.h>
#include <cuda.h>
#include <stdint.h>

namespace {

typedef __nv_bfloat16 bf16;
constexpr int SEQ = 2048, DM = 512, FF = 1792;
constexpr int NTHREADS = 640;
constexpr int NSLOT = 5;
constexpr uint32_t POLYMASK = 0x57;

constexpr uint32_t SM_A     = 0;
constexpr uint32_t SM_RING  = 131072;
constexpr uint32_t SM_ONES  = SM_RING + 81920;
constexpr uint32_t SM_BIAS  = SM_ONES + 512;
constexpr uint32_t SM_MERGE = SM_BIAS + 2048;
constexpr uint32_t SM_RSTD  = SM_MERGE + 12288;
constexpr uint32_t SM_SHIFT = SM_RSTD + 512;
constexpr uint32_t SM_BAR   = SM_SHIFT + 2048;
constexpr uint32_t B_FULL1  = SM_BAR;
constexpr uint32_t B_EMPTY1 = B_FULL1 + 8 * 2 * NSLOT;
constexpr uint32_t B_KV     = B_EMPTY1 + 8 * NSLOT;
constexpr uint32_t B_FULL2  = B_KV + 64;
constexpr uint32_t B_OE     = B_FULL2 + 24;
constexpr uint32_t B_WO     = B_OE + 16;
constexpr uint32_t B_O      = B_WO + 8;
constexpr uint32_t B_EMPTY2 = B_O + 32;
constexpr uint32_t B_OEE    = B_EMPTY2 + 24;
constexpr uint32_t B_ADONE  = B_OEE + 16;
constexpr uint32_t B_K0     = B_ADONE + 8;
constexpr uint32_t B_SHIFT  = B_K0 + 8;
constexpr uint32_t SM_TOTAL = B_SHIFT + 8;
static_assert(SM_TOTAL <= 232448, "shared memory");

__device__ __align__(1024) uint8_t gQ[32 * SEQ * 32];
__device__ __align__(1024) uint8_t gKV[32 * 16 * 8192];
__device__ __align__(1024) uint8_t gH[32 * 28 * 8192];
__device__ __align__(1024) uint8_t gO[32 * 8 * 8192];
__device__ uint32_t gFlag[72 * 32];
constexpr int F_QKV = 0, F_H = 8, F_O = 40;
#define TSTAMP(role, i)

template<int TB, int SD> __device__ __forceinline__ void wg_rs_n24(float* d, const uint32_t* a, uint64_t db) {
  if (SD)
    asm volatile("wgmma.mma_async.sync.aligned.m64n24k16.f32.bf16.bf16 {%0,%1,%2,%3,%4,%5,%6,%7,%8,%9,%10,%11}, {%12,%13,%14,%15}, %16, %18, 1, 1, %17;"
      : "+f"(d[0]),"+f"(d[1]),"+f"(d[2]),"+f"(d[3]),"+f"(d[4]),"+f"(d[5]),"+f"(d[6]),"+f"(d[7]),"+f"(d[8]),"+f"(d[9]),"+f"(d[10]),"+f"(d[11])
      : "r"(a[0]), "r"(a[1]), "r"(a[2]), "r"(a[3]), "l"(db), "n"(TB), "n"(SD & 1));
  else
    asm volatile("wgmma.mma_async.sync.aligned.m64n24k16.f32.bf16.bf16 {%0,%1,%2,%3,%4,%5,%6,%7,%8,%9,%10,%11}, {%12,%13,%14,%15}, %16, 0, 1, 1, %17;"
      : "=f"(d[0]),"=f"(d[1]),"=f"(d[2]),"=f"(d[3]),"=f"(d[4]),"=f"(d[5]),"=f"(d[6]),"=f"(d[7]),"=f"(d[8]),"=f"(d[9]),"=f"(d[10]),"=f"(d[11])
      : "r"(a[0]), "r"(a[1]), "r"(a[2]), "r"(a[3]), "l"(db), "n"(TB));
}
template<int TB, int SD> __device__ __forceinline__ void wg_rs_n32(float* d, const uint32_t* a, uint64_t db) {
  if (SD)
    asm volatile("wgmma.mma_async.sync.aligned.m64n32k16.f32.bf16.bf16 {%0,%1,%2,%3,%4,%5,%6,%7,%8,%9,%10,%11,%12,%13,%14,%15}, {%16,%17,%18,%19}, %20, %22, 1, 1, %21;"
      : "+f"(d[0]),"+f"(d[1]),"+f"(d[2]),"+f"(d[3]),"+f"(d[4]),"+f"(d[5]),"+f"(d[6]),"+f"(d[7]),"+f"(d[8]),"+f"(d[9]),"+f"(d[10]),"+f"(d[11]),"+f"(d[12]),"+f"(d[13]),"+f"(d[14]),"+f"(d[15])
      : "r"(a[0]), "r"(a[1]), "r"(a[2]), "r"(a[3]), "l"(db), "n"(TB), "n"(SD & 1));
  else
    asm volatile("wgmma.mma_async.sync.aligned.m64n32k16.f32.bf16.bf16 {%0,%1,%2,%3,%4,%5,%6,%7,%8,%9,%10,%11,%12,%13,%14,%15}, {%16,%17,%18,%19}, %20, 0, 1, 1, %21;"
      : "=f"(d[0]),"=f"(d[1]),"=f"(d[2]),"=f"(d[3]),"=f"(d[4]),"=f"(d[5]),"=f"(d[6]),"=f"(d[7]),"=f"(d[8]),"=f"(d[9]),"=f"(d[10]),"=f"(d[11]),"=f"(d[12]),"=f"(d[13]),"=f"(d[14]),"=f"(d[15])
      : "r"(a[0]), "r"(a[1]), "r"(a[2]), "r"(a[3]), "l"(db), "n"(TB));
}
template<int TB, int SD> __device__ __forceinline__ void wg_rs_n64(float* d, const uint32_t* a, uint64_t db) {
  if (SD)
    asm volatile("wgmma.mma_async.sync.aligned.m64n64k16.f32.bf16.bf16 {%0,%1,%2,%3,%4,%5,%6,%7,%8,%9,%10,%11,%12,%13,%14,%15,%16,%17,%18,%19,%20,%21,%22,%23,%24,%25,%26,%27,%28,%29,%30,%31}, {%32,%33,%34,%35}, %36, %38, 1, 1, %37;"
      : "+f"(d[0]),"+f"(d[1]),"+f"(d[2]),"+f"(d[3]),"+f"(d[4]),"+f"(d[5]),"+f"(d[6]),"+f"(d[7]),"+f"(d[8]),"+f"(d[9]),"+f"(d[10]),"+f"(d[11]),"+f"(d[12]),"+f"(d[13]),"+f"(d[14]),"+f"(d[15]),"+f"(d[16]),"+f"(d[17]),"+f"(d[18]),"+f"(d[19]),"+f"(d[20]),"+f"(d[21]),"+f"(d[22]),"+f"(d[23]),"+f"(d[24]),"+f"(d[25]),"+f"(d[26]),"+f"(d[27]),"+f"(d[28]),"+f"(d[29]),"+f"(d[30]),"+f"(d[31])
      : "r"(a[0]), "r"(a[1]), "r"(a[2]), "r"(a[3]), "l"(db), "n"(TB), "n"(SD & 1));
  else
    asm volatile("wgmma.mma_async.sync.aligned.m64n64k16.f32.bf16.bf16 {%0,%1,%2,%3,%4,%5,%6,%7,%8,%9,%10,%11,%12,%13,%14,%15,%16,%17,%18,%19,%20,%21,%22,%23,%24,%25,%26,%27,%28,%29,%30,%31}, {%32,%33,%34,%35}, %36, 0, 1, 1, %37;"
      : "=f"(d[0]),"=f"(d[1]),"=f"(d[2]),"=f"(d[3]),"=f"(d[4]),"=f"(d[5]),"=f"(d[6]),"=f"(d[7]),"=f"(d[8]),"=f"(d[9]),"=f"(d[10]),"=f"(d[11]),"=f"(d[12]),"=f"(d[13]),"=f"(d[14]),"=f"(d[15]),"=f"(d[16]),"=f"(d[17]),"=f"(d[18]),"=f"(d[19]),"=f"(d[20]),"=f"(d[21]),"=f"(d[22]),"=f"(d[23]),"=f"(d[24]),"=f"(d[25]),"=f"(d[26]),"=f"(d[27]),"=f"(d[28]),"=f"(d[29]),"=f"(d[30]),"=f"(d[31])
      : "r"(a[0]), "r"(a[1]), "r"(a[2]), "r"(a[3]), "l"(db), "n"(TB));
}
template<int TB> __device__ __forceinline__ void wg_ss_n64(float* d, uint64_t da, uint64_t db) {
  asm volatile("wgmma.mma_async.sync.aligned.m64n64k16.f32.bf16.bf16 {%0,%1,%2,%3,%4,%5,%6,%7,%8,%9,%10,%11,%12,%13,%14,%15,%16,%17,%18,%19,%20,%21,%22,%23,%24,%25,%26,%27,%28,%29,%30,%31}, %32, %33, 1, 1, 1, 0, %34;"
    : "+f"(d[0]),"+f"(d[1]),"+f"(d[2]),"+f"(d[3]),"+f"(d[4]),"+f"(d[5]),"+f"(d[6]),"+f"(d[7]),"+f"(d[8]),"+f"(d[9]),"+f"(d[10]),"+f"(d[11]),"+f"(d[12]),"+f"(d[13]),"+f"(d[14]),"+f"(d[15]),"+f"(d[16]),"+f"(d[17]),"+f"(d[18]),"+f"(d[19]),"+f"(d[20]),"+f"(d[21]),"+f"(d[22]),"+f"(d[23]),"+f"(d[24]),"+f"(d[25]),"+f"(d[26]),"+f"(d[27]),"+f"(d[28]),"+f"(d[29]),"+f"(d[30]),"+f"(d[31])
    : "l"(da), "l"(db), "n"(TB));
}
template<int TB> __device__ __forceinline__ void wg_ss_n128(float* d, uint64_t da, uint64_t db) {
  asm volatile("wgmma.mma_async.sync.aligned.m64n128k16.f32.bf16.bf16 {%0,%1,%2,%3,%4,%5,%6,%7,%8,%9,%10,%11,%12,%13,%14,%15,%16,%17,%18,%19,%20,%21,%22,%23,%24,%25,%26,%27,%28,%29,%30,%31,%32,%33,%34,%35,%36,%37,%38,%39,%40,%41,%42,%43,%44,%45,%46,%47,%48,%49,%50,%51,%52,%53,%54,%55,%56,%57,%58,%59,%60,%61,%62,%63}, %64, %65, 1, 1, 1, 0, %66;"
    : "+f"(d[0]),"+f"(d[1]),"+f"(d[2]),"+f"(d[3]),"+f"(d[4]),"+f"(d[5]),"+f"(d[6]),"+f"(d[7]),"+f"(d[8]),"+f"(d[9]),"+f"(d[10]),"+f"(d[11]),"+f"(d[12]),"+f"(d[13]),"+f"(d[14]),"+f"(d[15]),"+f"(d[16]),"+f"(d[17]),"+f"(d[18]),"+f"(d[19]),"+f"(d[20]),"+f"(d[21]),"+f"(d[22]),"+f"(d[23]),"+f"(d[24]),"+f"(d[25]),"+f"(d[26]),"+f"(d[27]),"+f"(d[28]),"+f"(d[29]),"+f"(d[30]),"+f"(d[31]),"+f"(d[32]),"+f"(d[33]),"+f"(d[34]),"+f"(d[35]),"+f"(d[36]),"+f"(d[37]),"+f"(d[38]),"+f"(d[39]),"+f"(d[40]),"+f"(d[41]),"+f"(d[42]),"+f"(d[43]),"+f"(d[44]),"+f"(d[45]),"+f"(d[46]),"+f"(d[47]),"+f"(d[48]),"+f"(d[49]),"+f"(d[50]),"+f"(d[51]),"+f"(d[52]),"+f"(d[53]),"+f"(d[54]),"+f"(d[55]),"+f"(d[56]),"+f"(d[57]),"+f"(d[58]),"+f"(d[59]),"+f"(d[60]),"+f"(d[61]),"+f"(d[62]),"+f"(d[63])
    : "l"(da), "l"(db), "n"(TB));
}

__device__ __forceinline__ void wg_fence() { asm volatile("wgmma.fence.sync.aligned;" ::: "memory"); }
__device__ __forceinline__ void wg_commit() { asm volatile("wgmma.commit_group.sync.aligned;" ::: "memory"); }
template <int N> __device__ __forceinline__ void wg_wait() { asm volatile("wgmma.wait_group.sync.aligned %0;" ::"n"(N) : "memory"); }
template <int N> __device__ __forceinline__ void pin(float* r) {
#pragma unroll
  for (int i = 0; i < N; i++) asm volatile("" : "+f"(r[i])::"memory");
}
template <int N> __device__ __forceinline__ void clear(float* r) {
#pragma unroll
  for (int i = 0; i < N; i++) r[i] = 0.f;
  pin<N>(r);
}
template <int N> __device__ __forceinline__ void pin(uint32_t* r) {
#pragma unroll
  for (int i = 0; i < N; i++) asm volatile("" : "+r"(r[i])::"memory");
}
__device__ __forceinline__ constexpr uint64_t mkdesc(uint32_t addr, uint32_t lbo, uint32_t sbo, uint32_t swz) {
  return (uint64_t)((addr & 0x3FFFF) >> 4) | ((uint64_t)(lbo >> 4) << 16) | ((uint64_t)(sbo >> 4) << 32) | ((uint64_t)swz << 62);
}
__device__ __forceinline__ void mbar_init(uint32_t b, int c) { asm volatile("mbarrier.init.shared::cta.b64 [%0], %1;" ::"r"(b), "r"(c) : "memory"); }
__device__ __forceinline__ void mbar_expect(uint32_t b, int n) { asm volatile("mbarrier.arrive.expect_tx.shared::cta.b64 _, [%0], %1;" ::"r"(b), "r"(n) : "memory"); }
__device__ __forceinline__ void mbar_arrive(uint32_t b) { asm volatile("mbarrier.arrive.shared::cta.b64 _, [%0];" ::"r"(b) : "memory"); }
__device__ __forceinline__ bool mbar_try(uint32_t b, uint32_t ph) {
  uint32_t ok;
  asm volatile("{.reg .pred p; mbarrier.try_wait.parity.shared::cta.b64 p, [%1], %2; selp.u32 %0, 1, 0, p;}" : "=r"(ok) : "r"(b), "r"(ph) : "memory");
  return ok;
}
__device__ __forceinline__ void mbar_wait(uint32_t b, uint32_t ph) {
  if (mbar_try(b, ph)) return;
#pragma unroll 1
  for (int i = 0; i < (1 << 16); i++) {
    uint32_t ok;
    asm volatile("{.reg .pred p; mbarrier.try_wait.parity.shared::cta.b64 p, [%1], %2, 20000; selp.u32 %0, 1, 0, p;}" : "=r"(ok) : "r"(b), "r"(ph) : "memory");
    if (ok) return;
  }
  __trap();
}
__device__ __forceinline__ void bulk_load(uint32_t dst, const void* src, int bytes, uint32_t bar) {
  asm volatile("cp.async.bulk.shared::cluster.global.mbarrier::complete_tx::bytes [%0], [%1], %2, [%3];" ::"r"(dst), "l"(src), "r"(bytes), "r"(bar) : "memory");
}
__device__ __forceinline__ void tma_load(uint32_t dst, const CUtensorMap* m, int c0, int c1, uint32_t bar) {
  asm volatile("cp.async.bulk.tensor.2d.shared::cluster.global.mbarrier::complete_tx::bytes [%0], [%1, {%2, %3}], [%4];" ::"r"(dst), "l"(m), "r"(c0), "r"(c1), "r"(bar) : "memory");
}
__device__ __forceinline__ void tma_prefetch(const CUtensorMap* m, int c0, int c1) {
  asm volatile("cp.async.bulk.prefetch.tensor.2d.L2.global [%0, {%1, %2}];" ::"l"(m), "r"(c0), "r"(c1) : "memory");
}
__device__ __forceinline__ bool elect() {
  uint32_t r;
  asm volatile("{.reg .pred p; elect.sync _|p, 0xffffffff; selp.u32 %0, 1, 0, p;}" : "=r"(r));
  return r;
}
__device__ __forceinline__ void bar_sync(int id, int n) { asm volatile("bar.sync %0, %1;" ::"r"(id), "r"(n) : "memory"); }
__device__ __forceinline__ void bar_arrive(int id, int n) { asm volatile("bar.arrive %0, %1;" ::"r"(id), "r"(n) : "memory"); }
__device__ __forceinline__ bool bar_or(int id, int n, bool v) {
  uint32_t r;
  asm volatile("{.reg .pred p, q; setp.ne.u32 q, %3, 0; bar.red.or.pred p, %1, %2, q; selp.u32 %0, 1, 0, p;}" : "=r"(r) : "r"(id), "r"(n), "r"((uint32_t)v) : "memory");
  return r;
}
__device__ __forceinline__ void flag_add(int f) { asm volatile("red.release.gpu.global.add.u32 [%0], 1;" ::"l"(gFlag + f * 32) : "memory"); }
__device__ __forceinline__ void flag_wait(int f, uint32_t target, uint32_t ns) {
#pragma unroll 1
  for (int i = 0; i < (1 << 22); i++) {
    uint32_t v;
    asm volatile("ld.acquire.gpu.global.u32 %0, [%1];" : "=r"(v) : "l"(gFlag + f * 32) : "memory");
    if ((int)(v - target) >= 0) { asm volatile("fence.proxy.async.global;" ::: "memory"); return; }
    __nanosleep(ns);
  }
  __trap();
}
__device__ __forceinline__ float ex2(float x) { float y; asm("ex2.approx.ftz.f32 %0, %1;" : "=f"(y) : "f"(x)); return y; }
__device__ __forceinline__ float rcp(float x) { float y; asm("rcp.approx.ftz.f32 %0, %1;" : "=f"(y) : "f"(x)); return y; }
__device__ __forceinline__ uint32_t packbf(float lo, float hi) { uint32_t d; asm("cvt.rn.bf16x2.f32 %0, %1, %2;" : "=r"(d) : "f"(hi), "f"(lo)); return d; }
__device__ __forceinline__ float bfr(float x) { return __bfloat162float(__float2bfloat16(x)); }
__device__ __forceinline__ uint32_t hmul(uint32_t a, uint32_t b) { uint32_t d; asm("mul.rn.bf16x2 %0, %1, %2;" : "=r"(d) : "r"(a), "r"(b)); return d; }
__device__ __forceinline__ uint32_t hadd(uint32_t a, uint32_t b) { uint32_t d; asm("add.rn.bf16x2 %0, %1, %2;" : "=r"(d) : "r"(a), "r"(b)); return d; }
__device__ __forceinline__ uint32_t hsub(uint32_t a, uint32_t b) { uint32_t d; asm("sub.rn.bf16x2 %0, %1, %2;" : "=r"(d) : "r"(a), "r"(b)); return d; }
__device__ __forceinline__ void hmma(float* c, const uint4& a, uint32_t b0, uint32_t b1) {
  asm("mma.sync.aligned.m16n8k16.row.col.f32.bf16.bf16.f32 {%0,%1,%2,%3},{%4,%5,%6,%7},{%8,%9},{%0,%1,%2,%3};"
      : "+f"(c[0]), "+f"(c[1]), "+f"(c[2]), "+f"(c[3]) : "r"(a.x), "r"(a.y), "r"(a.z), "r"(a.w), "r"(b0), "r"(b1));
}
constexpr float LOG2E = 1.4426950408889634f;

__device__ __forceinline__ uint32_t exp_poly(float lo, float hi, uint32_t half2) {
  uint32_t u, mh, p;
  asm("cvt.pack.sat.s16.s32 %0, %1, %2;" : "=r"(u) : "r"(__float_as_uint(hi)), "r"(__float_as_uint(lo)));
  asm("lop3.b32 %0, %1, 0x007F007F, %2, 0xEA;" : "=r"(mh) : "r"(u), "r"(half2));
  asm("fma.rn.bf16x2 %0, %1, %2, %3;" : "=r"(p) : "r"(u), "r"(mh), "r"(u & 0xFF80FF80u));
  return p;
}
__device__ __forceinline__ void softmax64(float* s, uint32_t* p, uint32_t half2) {
  pin<32>(s);
#pragma unroll
  for (int j = 0; j < 8; j++) {
#pragma unroll
    for (int r = 0; r < 2; r++) {
      const float a = s[4 * j + 2 * r], b = s[4 * j + 2 * r + 1];
      p[2 * j + r] = ((POLYMASK >> j) & 1) ? exp_poly(a, b, half2) : packbf(ex2(a), ex2(b));
    }
  }
  pin<16>(p);
}

template <int NT> __device__ __forceinline__ void tile_max(float* s, float* m) {
  pin<4 * NT>(s);
#pragma unroll
  for (int j = 0; j < NT; j++) {
    float* mm = m + (((POLYMASK >> j) & 1) ? 0 : 2);
    mm[0] = fmaxf(mm[0], fmaxf(s[4 * j], s[4 * j + 1]));
    mm[1] = fmaxf(mm[1], fmaxf(s[4 * j + 2], s[4 * j + 3]));
  }
}
__device__ __forceinline__ float shift_of(float mpoly, float mmufu) {
  float v = fmaxf(mmufu, (mpoly * 0x1p71f) * 0x1p71f);
  v = fmaxf(v, __shfl_xor_sync(~0u, v, 1));
  v = fmaxf(v, __shfl_xor_sync(~0u, v, 2));
  return __fadd_rn(__fadd_rn(12582952.f, -v), -12582912.f);
}
__device__ __forceinline__ uint32_t shift_frag(float shift, int t) {
  const float y = shift * 0x1p-71f;
  const float r1 = y - __uint_as_float(__float_as_uint(y) & 0xFFFF0000u);
  const float r2 = r1 - __uint_as_float(__float_as_uint(r1) & 0xFFFF0000u);
  const uint32_t w0 = __byte_perm(__float_as_uint(y), __float_as_uint(r1), 0x7632), w1 = __byte_perm(__float_as_uint(r2), 0x1C000000u, 0x7632);
  const uint32_t lo = t == 0 ? w0 : w1, hi = t == 2 ? 0x1C00u : 0u;
  return t < 2 ? lo : hi;
}

struct Tile { int kind, c0, c1; };
__device__ __forceinline__ Tile tile_of(int cg, int t) {
  const int c2 = cg >> 1;
  Tile r;
  if (cg & 1) {
    if (t == 0) { r.kind = 1; r.c0 = c2 * 128; r.c1 = r.c0 + 64; }
    else { r.kind = 2; r.c0 = r.c1 = (7 * c2 + 2 + t) * 64; }
  } else {
    if (t < 2) { r.kind = 0; r.c0 = 512 + c2 * 128 + t * 64; r.c1 = r.c0 + 512; }
    else { r.kind = 2; r.c0 = r.c1 = (7 * c2 + t - 2) * 64; }
  }
  return r;
}

__global__ void __launch_bounds__(NTHREADS, 1)
fused_kernel(const __grid_constant__ CUtensorMap mQKV, const __grid_constant__ CUtensorMap mW1, const __grid_constant__ CUtensorMap mW3,
             const __grid_constant__ CUtensorMap mW2, const __grid_constant__ CUtensorMap mWO, const __grid_constant__ CUtensorMap mX,
             const bf16* __restrict__ x, bf16* __restrict__ out,
             uint32_t zero) {
  extern __shared__ __align__(1024) uint8_t smem[];
  constexpr uint32_t sb = 1024;
  if ((uint32_t)__cvta_generic_to_shared(smem) != sb) __trap();
  const int tid = threadIdx.x, lane = tid & 31, g = lane >> 2, t = lane & 3;
  const int warp = __shfl_sync(~0u, tid >> 5, 0), wg = warp >> 2, w = warp & 3;
  const int b = blockIdx.x;
  const int rb = (b >> 5) * 4 + (b & 3), cg = (b >> 2) & 7;
  const int head = b >> 2, qb = b & 3;
  const int cb = b & 7;
  const int rEarly = (b >> 5) * 8 + ((0x3052 >> ((b >> 1) & 12)) & 7), rLate = (b >> 5) * 8 + ((0x6741 >> ((b >> 1) & 12)) & 7);

  if (wg < 4) TSTAMP(wg, 0);
  if (warp == 0) {
    if (elect()) {
#pragma unroll
      for (int j = 0; j < 8; j++) mbar_init(sb + B_KV + 8 * j, 1);
      asm volatile("fence.mbarrier_init.release.cluster;" ::: "memory");
#pragma unroll
      for (int j = 0; j < 8; j++) {
        mbar_expect(sb + B_KV + 8 * j, 16384);
        tma_load(sb + SM_A + j * 16384, &mX, j * 64, rb * 128, sb + B_KV + 8 * j);
      }
    }
    __syncwarp();
  }
  if (wg == 4) {
    asm volatile("setmaxnreg.dec.sync.aligned.u32 24;");
    if (w == 0) {
      TSTAMP(2, 6);
      if (elect()) {
#pragma unroll
        for (int i = 0; i < 2 * NSLOT; i++) mbar_init(sb + B_FULL1 + 8 * i, 1);
#pragma unroll
        for (int i = 0; i < NSLOT; i++) mbar_init(sb + B_EMPTY1 + 8 * i, 8);
#pragma unroll
        for (int i = 8; i < 26; i++) mbar_init(sb + B_KV + 8 * i, i < 18 ? 1 : i < 23 ? 4 : i == 23 ? 12 : i == 24 ? 1 : 8);
        asm volatile("fence.mbarrier_init.release.cluster;" ::: "memory");
      }
      __syncwarp();
      bar_arrive(1, 544);
      uint32_t epoch = 0;
      TSTAMP(2, 7);
      int slot = 0;
      uint32_t ph = 1;
#pragma unroll 1
      for (int tI = 0; tI < 5; tI++) {
        const Tile tl = tile_of(cg, tI);
        const CUtensorMap *m0 = tl.kind == 2 ? &mW1 : &mQKV, *m1 = tl.kind == 2 ? &mW3 : &mQKV;
#pragma unroll 1
        for (int k = 0; k < 8; k++) {
          const uint32_t full = sb + B_FULL1 + 8 * ((tI & 1) * NSLOT + slot), dst = sb + SM_RING + slot * 16384;
          if (tI == 4 && k == 0) {
            epoch = (epoch >> 5) + 1;
            flag_wait(F_QKV + (head >> 2), epoch * 32, 32);
            if (elect()) {
              mbar_expect(sb + B_K0, 1024);
              bulk_load(sb + SM_MERGE, gKV + (size_t)head * 131072, 1024, sb + B_K0);
            }
          }
          if (tI == 0 && k == NSLOT) {
            asm volatile("ld.relaxed.gpu.global.u32 %0, [%1];" : "=r"(epoch) : "l"(gFlag + F_O * 32) : "memory");
            const int i = 2 * NSLOT + rb + lane * 16;
            if (i < 80) {
              const Tile tp = tile_of(cg, i >> 4);
              tma_prefetch((i & 1) ? (tp.kind == 2 ? &mW3 : &mQKV) : (tp.kind == 2 ? &mW1 : &mQKV), (i & 1) ? tp.c1 : tp.c0, ((i >> 1) & 7) * 64);
            }
            __syncwarp();
          }
          mbar_wait(sb + B_EMPTY1 + 8 * slot, ph);
          if (elect()) {
            mbar_expect(full, 16384);
            tma_load(dst, m0, tl.c0, k * 64, full);
            tma_load(dst + 8192, m1, tl.c1, k * 64, full);
          }
          if (++slot == NSLOT) { slot = 0; ph ^= 1; }
        }
      }
#pragma unroll 1
      for (int j = 0; j < 8; j++) {
        if (j >= 8 - NSLOT) {
          mbar_wait(sb + B_EMPTY1 + 8 * slot, ph);
          if (++slot == NSLOT) { slot = 0; ph ^= 1; }
        }
        if (elect()) {
          mbar_expect(sb + B_KV + 8 * j, 16384);
          bulk_load(sb + SM_A + j * 16384, gKV + (size_t)head * 131072 + j * 16384, 16384, sb + B_KV + 8 * j);
        }
      }
      flag_wait(F_H + rEarly, epoch * 28, 100);
      flag_wait(F_H + rLate, epoch * 28, 100);
      slot = 0; ph = 1;
#pragma unroll 1
      for (int n = 0; n < 31; n++) {
        const uint32_t full = sb + B_FULL2 + 8 * slot, dst = sb + SM_RING + slot * 24576;
        mbar_wait(sb + B_EMPTY2 + 8 * slot, ph);
        if (n < 28 && elect()) {
          mbar_expect(full, 24576);
          tma_load(dst, &mW2, cb * 64, n * 64, full);
          bulk_load(dst + 8192, gH + (size_t)(rEarly * 28 + n) * 8192, 8192, full);
          bulk_load(dst + 16384, gH + (size_t)(rLate * 28 + n) * 8192, 8192, full);
        }
        if (++slot == 3) { slot = 0; ph ^= 1; }
      }
      if (elect()) {
        mbar_expect(sb + B_WO, 65536);
#pragma unroll 1
        for (int k = 0; k < 8; k++) tma_load(sb + SM_RING + k * 8192, &mWO, cb * 64, k * 64, sb + B_WO);
      }
      flag_wait(F_O + rEarly, epoch * 32, 200);
#pragma unroll 1
      for (int n = 0; n < 8; n++) {
        mbar_wait(sb + B_OEE + 8 * (n & 1), ((n >> 1) & 1) ^ 1);
        if (elect()) {
          mbar_expect(sb + B_OE + 8 * (n & 1), 8192);
          bulk_load(sb + SM_RING + 65536 + (n & 1) * 8192, gO + (size_t)(rEarly * 8 + n) * 8192, 8192, sb + B_OE + 8 * (n & 1));
        }
      }
      mbar_wait(sb + B_ADONE, 0);
      flag_wait(F_O + rLate, epoch * 32, 20);
      if (elect()) {
#pragma unroll
        for (int i = 0; i < 4; i++) {
          mbar_expect(sb + B_O + 8 * i, 16384);
          bulk_load(sb + SM_A + i * 16384, gO + (size_t)rLate * 65536 + i * 16384, 16384, sb + B_O + 8 * i);
        }
      }
    } else {
      if (w < 3) {
#pragma unroll 1
        for (int tI = w - 1; tI < 5; tI += 2) {
          const Tile tl = tile_of(cg, tI);
          bar_sync(3 + w, 288);
          if (lane < (tl.kind ? 2 : 1)) flag_add(tl.kind == 2 ? F_H + rb * 2 + lane : F_QKV + ((tl.c0 >> 6) & 7) + lane);
          __syncwarp();
        }
      }
#pragma unroll 1
      for (int i = 0; i < (w == 2 ? 2 : 3); i++) {
        bar_sync(12 + w, 160);
        if (lane == 0) flag_add(F_O + qb * 8 + (((w == 1 ? 0x102 : w == 2 ? 0x43 : 0x765) >> (i * 4)) & 7));
        __syncwarp();
      }
    }
    return;
  }

  asm volatile("setmaxnreg.inc.sync.aligned.u32 112;");

  {
    if (tid < 128) ((uint32_t*)(smem + SM_ONES))[tid] = 0x3F803F80u;
    {
      const int n = tid >> 3, k = (tid & 7) * 2;
      const bool poly = (POLYMASK >> (n >> 3)) & 1;
      const float cm = -127.f + 0.5849625f - 0.0020f, chi = bfr(cm), clo = cm - chi, sc = poly ? 0x1p-71f : 0x1p71f;
      float v0 = 0.f, v1 = 0.f;
      if (k == 0) { v0 = sc; v1 = sc; }
      if (k == 2) { v0 = sc; v1 = poly ? 0.f : chi * sc; }
      if (k == 4) { v0 = poly ? 0.f : clo * sc; }
      *(uint32_t*)(smem + SM_BIAS + n * 32 + (((k >> 3) ^ ((n >> 2) & 1)) << 4) + (k & 7) * 2) = packbf(v0, v1);
    }
    float cs[4] = {0.f, 0.f, 0.f, 0.f}, ca[4] = {0.f, 0.f, 0.f, 0.f}, cb[4] = {0.f, 0.f, 0.f, 0.f};
    uint4 xv[16];
    const int row = warp * 8 + g;
    uint8_t* xs = smem + SM_A + row * 128;
    const int xo0 = (((4 * (g & 1) + t) ^ g) << 4), xo1 = xo0 ^ 64;
    bar_sync(2, 512);
#pragma unroll
    for (int j = 0; j < 16; j++) {
      if ((j & 1) == 0) mbar_wait(sb + B_KV + 4 * j, 0);
      if (j == 0 && wg == 3) TSTAMP(3, 7);
      if (j == 8 && wg == 3) TSTAMP(3, 13);
      if (j == 14 && wg == 3) TSTAMP(3, 14);
      xv[j] = *(const uint4*)(xs + (j >> 1) * 16384 + ((j & 1) ? xo1 : xo0));
      hmma(cs, xv[j], 0x3F803F80u, 0x3F803F80u);
      hmma(ca, xv[j], xv[j].x, xv[j].z);
      hmma(cb, xv[j], xv[j].y, xv[j].w);
    }
    const float mean = (cs[0] + cs[2]) * (1.f / DM);
    const uint32_t m2 = packbf(mean, mean);
    if (m2 != 0x12345678) TSTAMP(4, wg);
#pragma unroll
    for (int j = 0; j < 16; j++)
      *(uint4*)(xs + (j >> 1) * 16384 + ((j & 1) ? xo1 : xo0)) = make_uint4(hsub(xv[j].x, m2), hsub(xv[j].y, m2), hsub(xv[j].z, m2), hsub(xv[j].w, m2));
    {
      const float var = fmaxf(((g & 1) ? ca[1] + cb[3] : ca[0] + cb[2]) * (1.f / DM) - mean * mean, 0.f);
      float sd;
      asm("sqrt.approx.f32 %0, %1;" : "=f"(sd) : "f"(bfr(bfr(var) + 1e-5f)));
      if (t == (g >> 1)) ((float*)(smem + SM_RSTD))[row] = rcp(bfr(sd));
    }
    TSTAMP(4, 4 + wg);
    asm volatile("fence.proxy.async.shared::cta;" ::: "memory");
    bar_sync(1, 544);
  }
  TSTAMP(wg, 1);
  const int pair = wg >> 1, half = wg & 1;

  const uint8_t* qbase = gQ + (size_t)head * 65536 + (size_t)(qb * 512 + w * 16 + g) * 32 + t * 4;
  auto load_q = [&](uint32_t* q, int rbl) {
    const uint32_t* qp = (const uint32_t*)(qbase + rbl * 2048);
    q[0] = __ldcg(qp); q[1] = __ldcg(qp + 64); q[2] = __ldcg(qp + 4); q[3] = __ldcg(qp + 68);
  };
  uint32_t q4[16];
  {
    uint32_t par = 0;
    const uint64_t dA0 = mkdesc(sb + SM_A + half * 8192, 16, 1024, 1), dB0 = mkdesc(sb + SM_RING, 8192, 1024, 1);
#pragma unroll 1
    for (int tI = pair; tI < 5; tI += 2) {
      float acc[64];
      clear<64>(acc);
      int slot = (tI * 8) % NSLOT, prev = 0;
#pragma unroll 1
      for (int k = 0; k < 8; k++) {
        mbar_wait(sb + B_FULL1 + 8 * (pair * NSLOT + slot), (par >> slot) & 1);
        par ^= 1u << slot;
        if (tI == 0 && wg == 0) TSTAMP(4, 8 + k);
        const uint64_t dA = dA0 + k * 1024, dB = dB0 + slot * 1024;
        wg_fence();
        wg_ss_n128<1>(acc, dA, dB);
        wg_ss_n128<1>(acc, dA + 2, dB + 128);
        wg_ss_n128<1>(acc, dA + 4, dB + 256);
        wg_ss_n128<1>(acc, dA + 6, dB + 384);
        wg_commit();
        if (k > 0) {
          wg_wait<1>();
          if (lane == 0) mbar_arrive(sb + B_EMPTY1 + 8 * prev);
        }
        prev = slot;
        if (++slot == NSLOT) slot = 0;
      }
      wg_wait<0>();
      if (lane == 0) mbar_arrive(sb + B_EMPTY1 + 8 * prev);
      pin<64>(acc);
      TSTAMP(wg, 2 + (tI >> 1) * 2);
      if (tI == 3) {
        mbar_wait(sb + B_K0, 0);
#pragma unroll
        for (int i = 0; i < 4; i++) load_q(q4 + 4 * i, half * 4 + i);
      }
      const Tile tl = tile_of(cg, tI);
      const int lrow = half * 64 + w * 16 + g;
      const float r0 = ((const float*)(smem + SM_RSTD))[lrow], r1 = ((const float*)(smem + SM_RSTD))[lrow + 8];
      if (tl.kind == 2) {
        uint32_t* hp = (uint32_t*)(gH + (size_t)((rb * 2 + half) * 28 + (tl.c0 >> 6)) * 8192 + w * 256) + lane;
#pragma unroll
        for (int j = 0; j < 8; j++) {
#pragma unroll
          for (int r = 0; r < 2; r++) {
            const float rs = r ? r1 : r0, e = -LOG2E * rs, q = rs * rs;
            const float g0 = acc[4 * j + 2 * r], g1 = acc[4 * j + 2 * r + 1];
            const float h0 = (g0 * q) * acc[32 + 4 * j + 2 * r] * rcp(1.f + ex2(g0 * e));
            const float h1 = (g1 * q) * acc[33 + 4 * j + 2 * r] * rcp(1.f + ex2(g1 * e));
            hp[j * 256 + r * 32] = packbf(h0, h1);
          }
        }
      } else {
        const int hg = (tl.c0 >> 6) & 7;
#pragma unroll
        for (int u = 0; u < 2; u++) {
#pragma unroll
          for (int r = 0; r < 2; r++) {
            float sc = r ? r1 : r0;
            uint8_t* p;
            size_t hs;
            if (tl.kind == 1) {
              sc *= 0.25f * LOG2E * 0x1p-71f;
              p = gQ + (size_t)(hg + u) * 4 * 65536 + (size_t)(rb * 128 + lrow + r * 8) * 32 + t * 8;
              hs = 65536;
            } else {
              if (u == 0) sc *= ((POLYMASK >> (2 * w + r)) & 1) ? 0x1p-71f : 0x1p71f;
              p = gKV + (size_t)hg * 4 * 131072 + rb * 8192 + u * 4096 + (lrow + r * 8) * 32 + ((t * 8) ^ ((g & 4) << 2));
              hs = 131072;
            }
#pragma unroll
            for (int hh = 0; hh < 4; hh++) {
              const float* a = acc + u * 32 + hh * 8 + 2 * r;
              *(uint2*)(p + hh * hs) = make_uint2(packbf(a[0] * sc, a[1] * sc), packbf(a[4] * sc, a[5] * sc));
            }
          }
        }
      }
      bar_arrive(4 + pair, 288);
      TSTAMP(wg, 3 + (tI >> 1) * 2);
    }
  }

  if (pair == 1) {
    float s[64];
    wg_fence();
#pragma unroll
    for (int i = 0; i < 4; i++) wg_rs_n32<0, 0>(s + 16 * i, q4 + 4 * i, mkdesc(sb + SM_MERGE, 16, 256, 3));
    wg_commit();
    wg_wait<0>();
#pragma unroll
    for (int i = 0; i < 4; i++) {
      float m[4] = {-INFINITY, -INFINITY, -INFINITY, -INFINITY};
      tile_max<4>(s + 16 * i, m);
      const float s0 = shift_of(m[0], m[2]), s1 = shift_of(m[1], m[3]);
      if (t < 2) ((float*)(smem + SM_SHIFT))[(half * 4 + i) * 64 + w * 16 + t * 8 + g] = t ? s1 : s0;
    }
    __syncwarp();
    if (lane == 0) mbar_arrive(sb + B_SHIFT);
    TSTAMP(wg, 15);
  }

  if (wg < 3) {
    asm volatile("setmaxnreg.inc.sync.aligned.u32 120;");
    constexpr uint64_t VS = (uint64_t)(32 - (32LL << 16));
    const uint32_t half2 = 0x3F003F00u + zero;
    const uint64_t dBias = mkdesc(sb + SM_BIAS, 16, 256, 3);
    const uint64_t dV0 = mkdesc(sb + SM_A + 4096, SM_ONES - SM_A - 4096, 256, 3);
    const float* shifts = (const float*)(smem + SM_SHIFT) + w * 16 + g;
#define SEG(r, c0, cl, mode) (uint64_t)((r) | (c0) << 3 | (cl) << 7 | (mode) << 11 | 1 << 13)
    uint64_t segs = wg == 0   ? SEG(2, 5, 15, 2) | SEG(0, 0, 15, 0) << 16 | SEG(1, 0, 15, 0) << 32
                    : wg == 1 ? SEG(2, 0, 4, 1) | SEG(5, 11, 15, 1) << 16 | SEG(3, 0, 15, 0) << 32 | SEG(4, 0, 15, 0) << 48
                              : SEG(5, 0, 10, 2) | SEG(6, 0, 15, 0) << 16 | SEG(7, 0, 15, 0) << 32;
    uint32_t q[4], qa[4], p0[16], p1[16];
    float s[32], o[12], shift[2];
    clear<32>(s);
    int ready = wg == 0 ? 2 : 0;
    mbar_wait(sb + B_SHIFT, 0);
    load_q(q, segs & 7);
    shift[0] = shifts[(segs & 7) * 64];
    shift[1] = shifts[(segs & 7) * 64 + 8];
    qa[2] = zero & q[0];
    qa[3] = zero & q[1];
    mbar_wait(sb + B_KV + 8 * ready, 1);
    TSTAMP(wg, 8);
    bool exact = false;
    bool primed = false;
#pragma unroll 1
    while (true) {
      const uint32_t sg = (uint32_t)segs, sn = sg >> 16;
      const int rbl = sg & 7, c0 = (sg >> 3) & 15, cl = (sg >> 7) & 15, mode = (sg >> 11) & 3;
      uint64_t c = dV0 + (uint64_t)c0 * (16 * VS);
      if (!primed) {
        if (exact) {
          load_q(q, rbl);
          float m[4] = {-INFINITY, -INFINITY, -INFINITY, -INFINITY};
#pragma unroll 1
          for (int i = 2 * c0; i < 2 * cl + 2; i++) {
            wg_fence();
            wg_rs_n64<0, 2>(s, q, dV0 - 256 + (i >> 1) * 512 + (i & 1) * 128);
            wg_commit();
            wg_wait<0>();
            tile_max<8>(s, m);
          }
          shift[0] = shift_of(m[0], m[2]);
          shift[1] = shift_of(m[1], m[3]);
        }
        qa[0] = shift_frag(shift[0], t);
        qa[1] = shift_frag(shift[1], t);
        wg_fence();
        wg_rs_n64<0, 2>(s, qa, dBias);
        wg_rs_n64<0, 1>(s, q, c - 256);
        wg_commit();
        wg_wait<0>();
      }
      uint32_t qn[4];
      load_q(qn, sn & 7);
      clear<12>(o);
      auto first_half = [&]() {
        softmax64(s, p0, half2);
        wg_fence();
        wg_rs_n64<0, 2>(s, qa, dBias);
        wg_rs_n64<0, 1>(s, q, c - 128);
        wg_commit();
#pragma unroll
        for (int k = 0; k < 4; k++) wg_rs_n24<1, 1>(o, p0 + 4 * k, c + k * VS);
        wg_commit();
        wg_wait<1>();
        softmax64(s, p1, half2);
      };
      auto second_half = [&](uint64_t dKnext) {
        wg_fence();
        wg_rs_n64<0, 2>(s, qa, dBias);
        wg_rs_n64<0, 1>(s, q, dKnext);
        wg_commit();
#pragma unroll
        for (int k = 0; k < 4; k++) wg_rs_n24<1, 1>(o, p1 + 4 * k, c + (4 + k) * VS);
        wg_commit();
      };
#pragma unroll 1
      for (int ci = c0; ci < cl;) {
        if (ready < 7) mbar_wait(sb + B_KV + 8 * ++ready, 1);
        ci = ready >= 7 ? cl : min(cl, 2 * ready);
        const uint32_t cend = (uint32_t)dV0 + ci * (uint32_t)(16 * VS);
#pragma unroll 1
        do {
          first_half();
          second_half(c + 256);
          c += 16 * VS;
          wg_wait<1>();
        } while ((uint32_t)c != cend);
      }
      if (ready < 8) {
#pragma unroll 1
        for (int j = 0; j < 8; j++) mbar_wait(sb + B_KV + 8 * j, 1);
        ready = 8;
      }
      const float bias[2] = {shift[0], shift[1]};
      shift[0] = shifts[(sn & 7) * 64];
      shift[1] = shifts[(sn & 7) * 64 + 8];
      first_half();
      qa[0] = shift_frag(shift[0], t);
      qa[1] = shift_frag(shift[1], t);
#pragma unroll
      for (int i = 0; i < 4; i++) q[i] = qn[i];
      pin<4>(q);
      pin<2>(qa);
      second_half(dV0 - 256 + ((sn >> 3) & 15) * 512);
      wg_wait<0>();
      pin<12>(o);
      exact = __all_sync(~0u, bar_or(10 + wg, 128, !exact && !(o[8] < 0x1p100f && o[10] < 0x1p100f)));
      primed = !exact;
      if (exact) continue;
      segs >>= 16;
      if (mode == 1) {
        float* mp = (float*)(smem + SM_MERGE + (rbl >> 2) * 6144) + (tid & 127);
        o[9] = bias[0]; o[11] = bias[1];
#pragma unroll
        for (int i = 0; i < 12; i++) mp[i * 128] = o[i];
        bar_arrive(8 + (rbl >> 2), 256);
        continue;
      }
      if (mode == 2) {
        const float* mp = (const float*)(smem + SM_MERGE + (wg >> 1) * 6144) + (tid & 127);
        bar_sync(8 + (wg >> 1), 256);
#pragma unroll
        for (int r = 0; r < 2; r++) {
          const float bo = mp[(9 + 2 * r) * 128], bm = fminf(bo, bias[r]);
          const float fa = ex2(0.5f * (bm - bias[r])), fb = ex2(0.5f * (bm - bo));
          o[2 * r] = o[2 * r] * fa * fa + mp[(2 * r) * 128] * fb * fb;
          o[2 * r + 1] = o[2 * r + 1] * fa * fa + mp[(2 * r + 1) * 128] * fb * fb;
          o[4 + 2 * r] = o[4 + 2 * r] * fa * fa + mp[(4 + 2 * r) * 128] * fb * fb;
          o[5 + 2 * r] = o[5 + 2 * r] * fa * fa + mp[(5 + 2 * r) * 128] * fb * fb;
          o[8 + 2 * r] = o[8 + 2 * r] * fa * fa + mp[(8 + 2 * r) * 128] * fb * fb;
        }
      }
      if (sn == 0 && lane == 0) mbar_arrive(sb + B_ADONE);
#pragma unroll
      for (int r = 0; r < 2; r++) {
        const float inv = rcp(o[8 + 2 * r]);
        const uint32_t a = packbf(o[2 * r] * inv, o[2 * r + 1] * inv), d = packbf(o[4 + 2 * r] * inv, o[5 + 2 * r] * inv);
        const uint32_t e = __shfl_xor_sync(~0u, (t & 2) ? a : d, 2);
        *(uint2*)(gO + (size_t)((qb * 8 + rbl) * 8 + (head >> 2)) * 8192 + ((head & 3) * 2 + (t & 1)) * 1024 + (2 * w + r) * 128 + g * 16 + (t & 2) * 4) =
            (t & 2) ? make_uint2(e, d) : make_uint2(a, e);
      }
      bar_arrive(13 + wg, 160);
      TSTAMP(wg, sn == 0 ? 11 : mode ? 9 : 10);
      if (sn == 0) break;
    }
  } else {
    asm volatile("setmaxnreg.dec.sync.aligned.u32 96;");
    uint32_t gate[32];
    const uint64_t dB0 = mkdesc(sb + SM_RING, 8192, 1024, 1);
    {
      const uint64_t dA0 = mkdesc(sb + SM_RING + 8192, 1024, 128, 0);
      float acc[64];
      clear<64>(acc);
      int slot = 0;
      uint32_t ph = 0;
#pragma unroll 1
      for (int n = 0; n < 28; n++) {
        mbar_wait(sb + B_FULL2 + 8 * slot, ph);
        const uint64_t dA = dA0 + slot * 1536, dB = dB0 + slot * 1536;
        wg_fence();
#pragma unroll
        for (int k = 0; k < 4; k++) {
          wg_ss_n64<1>(acc, dA + k * 128, dB + k * 128);
          wg_ss_n64<1>(acc + 32, dA + 512 + k * 128, dB + k * 128);
        }
        wg_commit();
        wg_wait<0>();
        if (lane == 0) mbar_arrive(sb + B_EMPTY2 + 8 * slot);
        if (++slot == 3) { slot = 0; ph ^= 1; }
      }
      pin<64>(acc);
#pragma unroll
      for (int i = 0; i < 32; i++) {
        const uint32_t f = packbf(acc[2 * i], acc[2 * i + 1]);
        const float f0 = __uint_as_float(f << 16), f1 = __uint_as_float(f & 0xFFFF0000u);
        gate[i] = packbf(f0 * rcp(1.f + ex2(-LOG2E * f0)), f1 * rcp(1.f + ex2(-LOG2E * f1)));
      }
      mbar_wait(sb + B_WO, 0);
    }
    TSTAMP(wg, 8);
#pragma unroll
    for (int pass = 0; pass < 2; pass++) {
      const size_t off = (size_t)((pass ? rLate : rEarly) * 64 + w * 16 + g) * DM + cb * 64 + (t & 1) * 8 + (t & 2) * 2;
      uint2 xr[8];
#pragma unroll
      for (int i = 0; i < 8; i++) xr[i] = __ldg((const uint2*)(x + off + (i & 1) * 8 * DM + (i >> 1) * 16));
      float acc[32];
      clear<32>(acc);
      if (pass == 0) {
        const uint64_t dA0 = mkdesc(sb + SM_RING + 65536, 1024, 128, 0);
#pragma unroll 1
        for (int n = 0; n < 8; n++) {
          mbar_wait(sb + B_OE + 8 * (n & 1), (n >> 1) & 1);
          wg_fence();
#pragma unroll
          for (int k = 0; k < 4; k++) wg_ss_n64<1>(acc, dA0 + (n & 1) * 512 + k * 128, dB0 + n * 512 + k * 128);
          wg_commit();
          wg_wait<0>();
          if (lane == 0) mbar_arrive(sb + B_OEE + 8 * (n & 1));
        }
      } else {
        mbar_wait(sb + B_ADONE, 0);
        const uint64_t dA = mkdesc(sb + SM_A, 1024, 128, 0);
#pragma unroll 1
        for (int n = 0; n < 4; n++) {
          mbar_wait(sb + B_O + 8 * n, 0);
          wg_fence();
#pragma unroll
          for (int k = 0; k < 8; k++) wg_ss_n64<1>(acc, dA + (n * 8 + k) * 128, dB0 + (n * 8 + k) * 128);
          wg_commit();
        }
        wg_wait<0>();
      }
      pin<32>(acc);
      TSTAMP(wg, 9 + 2 * pass);
#pragma unroll
      for (int i = 0; i < 8; i++) {
        const int ia = (i >> 1) * 4 + (i & 1), ib = ia + 2;
        const uint32_t ya = hmul(packbf(acc[2 * ia], acc[2 * ia + 1]), gate[pass * 16 + ia]);
        const uint32_t yb = hmul(packbf(acc[2 * ib], acc[2 * ib + 1]), gate[pass * 16 + ib]);
        const uint32_t e = __shfl_xor_sync(~0u, (t & 1) ? ya : yb, 1);
        const uint32_t lo = (t & 1) ? e : ya, hi = (t & 1) ? yb : e;
        *(uint2*)(out + off + (i & 1) * 8 * DM + (i >> 1) * 16) = make_uint2(hadd(xr[i].x, lo), hadd(xr[i].y, hi));
      }
      TSTAMP(wg, 10 + 2 * pass);
    }
  }
}

typedef CUresult (*EncodeFn)(CUtensorMap*, CUtensorMapDataType, cuuint32_t, void*, const cuuint64_t*, const cuuint64_t*, const cuuint32_t*,
                             const cuuint32_t*, CUtensorMapInterleave, CUtensorMapSwizzle, CUtensorMapL2promotion, CUtensorMapFloatOOBfill);

void make_map(EncodeFn enc, CUtensorMap* m, void* p, int rows, int cols, int boxrows = 64) {
  const cuuint64_t dims[2] = {(cuuint64_t)cols, (cuuint64_t)rows}, strides[1] = {(cuuint64_t)cols * 2};
  const cuuint32_t box[2] = {64, (cuuint32_t)boxrows}, es[2] = {1, 1};
  enc(m, CU_TENSOR_MAP_DATA_TYPE_BFLOAT16, 2, p, dims, strides, box, es, CU_TENSOR_MAP_INTERLEAVE_NONE, CU_TENSOR_MAP_SWIZZLE_128B,
      CU_TENSOR_MAP_L2_PROMOTION_L2_128B, CU_TENSOR_MAP_FLOAT_OOB_FILL_NONE);
}

}

extern "C" void kernel_launch(void* const* d_in, const int* in_sizes, int n_in, void* d_out, int out_size) {
  (void)in_sizes; (void)n_in; (void)out_size;
  void* fn = nullptr;
  cudaDriverEntryPointQueryResult qr;
  cudaGetDriverEntryPoint("cuTensorMapEncodeTiled", &fn, cudaEnableDefault, &qr);
  EncodeFn enc = (EncodeFn)fn;
  CUtensorMap mQKV, mW1, mW3, mW2, mWO, mX;
  make_map(enc, &mX, d_in[0], SEQ, DM, 128);
  make_map(enc, &mQKV, d_in[1], DM, 3 * DM);
  make_map(enc, &mWO, d_in[2], DM, DM);
  make_map(enc, &mW1, d_in[4], DM, FF);
  make_map(enc, &mW3, d_in[5], DM, FF);
  make_map(enc, &mW2, d_in[6], FF, DM);
  cudaFuncSetAttribute(fused_kernel, cudaFuncAttributeMaxDynamicSharedMemorySize, SM_TOTAL);
  fused_kernel<<<128, NTHREADS, SM_TOTAL>>>(mQKV, mW1, mW3, mW2, mWO, mX, (const bf16*)d_in[0], (bf16*)d_out, 0u);
}
```

```cpp
#include <cuda_runtime.h>
#include <cuda_bf16.h>
#include <cuda.h>
#include <stdint.h>

namespace {

typedef __nv_bfloat16 bf16;
constexpr int SEQ = 2048, DM = 512, FF = 1792;
constexpr int NTHREADS = 640;
constexpr int NSLOT = 5;
constexpr uint64_t PARITY1 = 0xaa6c6ce0e0ull;
constexpr uint32_t POLYMASK = 0x57;

constexpr uint32_t SM_A     = 0;
constexpr uint32_t SM_RING  = 131072;
constexpr uint32_t SM_ONES  = SM_RING + 81920;
constexpr uint32_t SM_BIAS  = SM_ONES + 512;
constexpr uint32_t SM_MERGE = SM_BIAS + 2048;
constexpr uint32_t SM_RSTD  = SM_MERGE + 12288;
constexpr uint32_t SM_SHIFT = SM_RSTD + 512;
constexpr uint32_t SM_BAR   = SM_SHIFT + 2048;
constexpr uint32_t B_FULL1  = SM_BAR;
constexpr uint32_t B_EMPTY1 = B_FULL1 + 8 * 2 * NSLOT;
constexpr uint32_t B_KV     = B_EMPTY1 + 8 * NSLOT;
constexpr uint32_t B_FULL2  = B_KV + 64;
constexpr uint32_t B_OE     = B_FULL2 + 24;
constexpr uint32_t B_WO     = B_OE + 16;
constexpr uint32_t B_O      = B_WO + 8;
constexpr uint32_t B_EMPTY2 = B_O + 32;
constexpr uint32_t B_OEE    = B_EMPTY2 + 24;
constexpr uint32_t B_ADONE  = B_OEE + 16;
constexpr uint32_t B_K0     = B_ADONE + 8;
constexpr uint32_t B_SHIFT  = B_K0 + 8;
constexpr uint32_t SM_TOTAL = B_SHIFT + 8;
static_assert(SM_TOTAL <= 232448, "shared memory");

constexpr int HS = 196608;
__device__ __align__(1024) uint8_t gQKV[32 * HS];
__device__ __align__(1024) uint8_t gH[32 * 28 * 8192];
__device__ __align__(1024) uint8_t gO[32 * 8 * 8192];
__device__ uint32_t gFlag[72 * 32];
constexpr int F_QKV = 0, F_H = 8, F_O = 40;
#define TSTAMP(role, i)

template<int TB, int SD> __device__ __forceinline__ void wg_rs_n24(float* d, const uint32_t* a, uint64_t db) {
  if (SD)
    asm volatile("wgmma.mma_async.sync.aligned.m64n24k16.f32.bf16.bf16 {%0,%1,%2,%3,%4,%5,%6,%7,%8,%9,%10,%11}, {%12,%13,%14,%15}, %16, %18, 1, 1, %17;"
      : "+f"(d[0]),"+f"(d[1]),"+f"(d[2]),"+f"(d[3]),"+f"(d[4]),"+f"(d[5]),"+f"(d[6]),"+f"(d[7]),"+f"(d[8]),"+f"(d[9]),"+f"(d[10]),"+f"(d[11])
      : "r"(a[0]), "r"(a[1]), "r"(a[2]), "r"(a[3]), "l"(db), "n"(TB), "n"(SD & 1));
  else
    asm volatile("wgmma.mma_async.sync.aligned.m64n24k16.f32.bf16.bf16 {%0,%1,%2,%3,%4,%5,%6,%7,%8,%9,%10,%11}, {%12,%13,%14,%15}, %16, 0, 1, 1, %17;"
      : "=f"(d[0]),"=f"(d[1]),"=f"(d[2]),"=f"(d[3]),"=f"(d[4]),"=f"(d[5]),"=f"(d[6]),"=f"(d[7]),"=f"(d[8]),"=f"(d[9]),"=f"(d[10]),"=f"(d[11])
      : "r"(a[0]), "r"(a[1]), "r"(a[2]), "r"(a[3]), "l"(db), "n"(TB));
}
template<int TB, int SD> __device__ __forceinline__ void wg_rs_n32(float* d, const uint32_t* a, uint64_t db) {
  if (SD)
    asm volatile("wgmma.mma_async.sync.aligned.m64n32k16.f32.bf16.bf16 {%0,%1,%2,%3,%4,%5,%6,%7,%8,%9,%10,%11,%12,%13,%14,%15}, {%16,%17,%18,%19}, %20, %22, 1, 1, %21;"
      : "+f"(d[0]),"+f"(d[1]),"+f"(d[2]),"+f"(d[3]),"+f"(d[4]),"+f"(d[5]),"+f"(d[6]),"+f"(d[7]),"+f"(d[8]),"+f"(d[9]),"+f"(d[10]),"+f"(d[11]),"+f"(d[12]),"+f"(d[13]),"+f"(d[14]),"+f"(d[15])
      : "r"(a[0]), "r"(a[1]), "r"(a[2]), "r"(a[3]), "l"(db), "n"(TB), "n"(SD & 1));
  else
    asm volatile("wgmma.mma_async.sync.aligned.m64n32k16.f32.bf16.bf16 {%0,%1,%2,%3,%4,%5,%6,%7,%8,%9,%10,%11,%12,%13,%14,%15}, {%16,%17,%18,%19}, %20, 0, 1, 1, %21;"
      : "=f"(d[0]),"=f"(d[1]),"=f"(d[2]),"=f"(d[3]),"=f"(d[4]),"=f"(d[5]),"=f"(d[6]),"=f"(d[7]),"=f"(d[8]),"=f"(d[9]),"=f"(d[10]),"=f"(d[11]),"=f"(d[12]),"=f"(d[13]),"=f"(d[14]),"=f"(d[15])
      : "r"(a[0]), "r"(a[1]), "r"(a[2]), "r"(a[3]), "l"(db), "n"(TB));
}
template<int TB, int SD> __device__ __forceinline__ void wg_rs_n64(float* d, const uint32_t* a, uint64_t db) {
  if (SD)
    asm volatile("wgmma.mma_async.sync.aligned.m64n64k16.f32.bf16.bf16 {%0,%1,%2,%3,%4,%5,%6,%7,%8,%9,%10,%11,%12,%13,%14,%15,%16,%17,%18,%19,%20,%21,%22,%23,%24,%25,%26,%27,%28,%29,%30,%31}, {%32,%33,%34,%35}, %36, %38, 1, 1, %37;"
      : "+f"(d[0]),"+f"(d[1]),"+f"(d[2]),"+f"(d[3]),"+f"(d[4]),"+f"(d[5]),"+f"(d[6]),"+f"(d[7]),"+f"(d[8]),"+f"(d[9]),"+f"(d[10]),"+f"(d[11]),"+f"(d[12]),"+f"(d[13]),"+f"(d[14]),"+f"(d[15]),"+f"(d[16]),"+f"(d[17]),"+f"(d[18]),"+f"(d[19]),"+f"(d[20]),"+f"(d[21]),"+f"(d[22]),"+f"(d[23]),"+f"(d[24]),"+f"(d[25]),"+f"(d[26]),"+f"(d[27]),"+f"(d[28]),"+f"(d[29]),"+f"(d[30]),"+f"(d[31])
      : "r"(a[0]), "r"(a[1]), "r"(a[2]), "r"(a[3]), "l"(db), "n"(TB), "n"(SD & 1));
  else
    asm volatile("wgmma.mma_async.sync.aligned.m64n64k16.f32.bf16.bf16 {%0,%1,%2,%3,%4,%5,%6,%7,%8,%9,%10,%11,%12,%13,%14,%15,%16,%17,%18,%19,%20,%21,%22,%23,%24,%25,%26,%27,%28,%29,%30,%31}, {%32,%33,%34,%35}, %36, 0, 1, 1, %37;"
      : "=f"(d[0]),"=f"(d[1]),"=f"(d[2]),"=f"(d[3]),"=f"(d[4]),"=f"(d[5]),"=f"(d[6]),"=f"(d[7]),"=f"(d[8]),"=f"(d[9]),"=f"(d[10]),"=f"(d[11]),"=f"(d[12]),"=f"(d[13]),"=f"(d[14]),"=f"(d[15]),"=f"(d[16]),"=f"(d[17]),"=f"(d[18]),"=f"(d[19]),"=f"(d[20]),"=f"(d[21]),"=f"(d[22]),"=f"(d[23]),"=f"(d[24]),"=f"(d[25]),"=f"(d[26]),"=f"(d[27]),"=f"(d[28]),"=f"(d[29]),"=f"(d[30]),"=f"(d[31])
      : "r"(a[0]), "r"(a[1]), "r"(a[2]), "r"(a[3]), "l"(db), "n"(TB));
}
template<int TB, int SD> __device__ __forceinline__ void wg_ss_n64(float* d, uint64_t da, uint64_t db) {
  if (SD)
    asm volatile("wgmma.mma_async.sync.aligned.m64n64k16.f32.bf16.bf16 {%0,%1,%2,%3,%4,%5,%6,%7,%8,%9,%10,%11,%12,%13,%14,%15,%16,%17,%18,%19,%20,%21,%22,%23,%24,%25,%26,%27,%28,%29,%30,%31}, %32, %33, 1, 1, 1, 0, %34;"
      : "+f"(d[0]),"+f"(d[1]),"+f"(d[2]),"+f"(d[3]),"+f"(d[4]),"+f"(d[5]),"+f"(d[6]),"+f"(d[7]),"+f"(d[8]),"+f"(d[9]),"+f"(d[10]),"+f"(d[11]),"+f"(d[12]),"+f"(d[13]),"+f"(d[14]),"+f"(d[15]),"+f"(d[16]),"+f"(d[17]),"+f"(d[18]),"+f"(d[19]),"+f"(d[20]),"+f"(d[21]),"+f"(d[22]),"+f"(d[23]),"+f"(d[24]),"+f"(d[25]),"+f"(d[26]),"+f"(d[27]),"+f"(d[28]),"+f"(d[29]),"+f"(d[30]),"+f"(d[31])
      : "l"(da), "l"(db), "n"(TB));
  else
    asm volatile("wgmma.mma_async.sync.aligned.m64n64k16.f32.bf16.bf16 {%0,%1,%2,%3,%4,%5,%6,%7,%8,%9,%10,%11,%12,%13,%14,%15,%16,%17,%18,%19,%20,%21,%22,%23,%24,%25,%26,%27,%28,%29,%30,%31}, %32, %33, 0, 1, 1, 0, %34;"
      : "=f"(d[0]),"=f"(d[1]),"=f"(d[2]),"=f"(d[3]),"=f"(d[4]),"=f"(d[5]),"=f"(d[6]),"=f"(d[7]),"=f"(d[8]),"=f"(d[9]),"=f"(d[10]),"=f"(d[11]),"=f"(d[12]),"=f"(d[13]),"=f"(d[14]),"=f"(d[15]),"=f"(d[16]),"=f"(d[17]),"=f"(d[18]),"=f"(d[19]),"=f"(d[20]),"=f"(d[21]),"=f"(d[22]),"=f"(d[23]),"=f"(d[24]),"=f"(d[25]),"=f"(d[26]),"=f"(d[27]),"=f"(d[28]),"=f"(d[29]),"=f"(d[30]),"=f"(d[31])
      : "l"(da), "l"(db), "n"(TB));
}
template<int TB, int SD> __device__ __forceinline__ void wg_ss_n128(float* d, uint64_t da, uint64_t db) {
  if (SD)
    asm volatile("wgmma.mma_async.sync.aligned.m64n128k16.f32.bf16.bf16 {%0,%1,%2,%3,%4,%5,%6,%7,%8,%9,%10,%11,%12,%13,%14,%15,%16,%17,%18,%19,%20,%21,%22,%23,%24,%25,%26,%27,%28,%29,%30,%31,%32,%33,%34,%35,%36,%37,%38,%39,%40,%41,%42,%43,%44,%45,%46,%47,%48,%49,%50,%51,%52,%53,%54,%55,%56,%57,%58,%59,%60,%61,%62,%63}, %64, %65, 1, 1, 1, 0, %66;"
      : "+f"(d[0]),"+f"(d[1]),"+f"(d[2]),"+f"(d[3]),"+f"(d[4]),"+f"(d[5]),"+f"(d[6]),"+f"(d[7]),"+f"(d[8]),"+f"(d[9]),"+f"(d[10]),"+f"(d[11]),"+f"(d[12]),"+f"(d[13]),"+f"(d[14]),"+f"(d[15]),"+f"(d[16]),"+f"(d[17]),"+f"(d[18]),"+f"(d[19]),"+f"(d[20]),"+f"(d[21]),"+f"(d[22]),"+f"(d[23]),"+f"(d[24]),"+f"(d[25]),"+f"(d[26]),"+f"(d[27]),"+f"(d[28]),"+f"(d[29]),"+f"(d[30]),"+f"(d[31]),"+f"(d[32]),"+f"(d[33]),"+f"(d[34]),"+f"(d[35]),"+f"(d[36]),"+f"(d[37]),"+f"(d[38]),"+f"(d[39]),"+f"(d[40]),"+f"(d[41]),"+f"(d[42]),"+f"(d[43]),"+f"(d[44]),"+f"(d[45]),"+f"(d[46]),"+f"(d[47]),"+f"(d[48]),"+f"(d[49]),"+f"(d[50]),"+f"(d[51]),"+f"(d[52]),"+f"(d[53]),"+f"(d[54]),"+f"(d[55]),"+f"(d[56]),"+f"(d[57]),"+f"(d[58]),"+f"(d[59]),"+f"(d[60]),"+f"(d[61]),"+f"(d[62]),"+f"(d[63])
      : "l"(da), "l"(db), "n"(TB));
  else
    asm volatile("wgmma.mma_async.sync.aligned.m64n128k16.f32.bf16.bf16 {%0,%1,%2,%3,%4,%5,%6,%7,%8,%9,%10,%11,%12,%13,%14,%15,%16,%17,%18,%19,%20,%21,%22,%23,%24,%25,%26,%27,%28,%29,%30,%31,%32,%33,%34,%35,%36,%37,%38,%39,%40,%41,%42,%43,%44,%45,%46,%47,%48,%49,%50,%51,%52,%53,%54,%55,%56,%57,%58,%59,%60,%61,%62,%63}, %64, %65, 0, 1, 1, 0, %66;"
      : "=f"(d[0]),"=f"(d[1]),"=f"(d[2]),"=f"(d[3]),"=f"(d[4]),"=f"(d[5]),"=f"(d[6]),"=f"(d[7]),"=f"(d[8]),"=f"(d[9]),"=f"(d[10]),"=f"(d[11]),"=f"(d[12]),"=f"(d[13]),"=f"(d[14]),"=f"(d[15]),"=f"(d[16]),"=f"(d[17]),"=f"(d[18]),"=f"(d[19]),"=f"(d[20]),"=f"(d[21]),"=f"(d[22]),"=f"(d[23]),"=f"(d[24]),"=f"(d[25]),"=f"(d[26]),"=f"(d[27]),"=f"(d[28]),"=f"(d[29]),"=f"(d[30]),"=f"(d[31]),"=f"(d[32]),"=f"(d[33]),"=f"(d[34]),"=f"(d[35]),"=f"(d[36]),"=f"(d[37]),"=f"(d[38]),"=f"(d[39]),"=f"(d[40]),"=f"(d[41]),"=f"(d[42]),"=f"(d[43]),"=f"(d[44]),"=f"(d[45]),"=f"(d[46]),"=f"(d[47]),"=f"(d[48]),"=f"(d[49]),"=f"(d[50]),"=f"(d[51]),"=f"(d[52]),"=f"(d[53]),"=f"(d[54]),"=f"(d[55]),"=f"(d[56]),"=f"(d[57]),"=f"(d[58]),"=f"(d[59]),"=f"(d[60]),"=f"(d[61]),"=f"(d[62]),"=f"(d[63])
      : "l"(da), "l"(db), "n"(TB));
}

__device__ __forceinline__ void wg_fence() { asm volatile("wgmma.fence.sync.aligned;" ::: "memory"); }
__device__ __forceinline__ void wg_commit() { asm volatile("wgmma.commit_group.sync.aligned;" ::: "memory"); }
template <int N> __device__ __forceinline__ void wg_wait() { asm volatile("wgmma.wait_group.sync.aligned %0;" ::"n"(N) : "memory"); }
template <int N> __device__ __forceinline__ void pin(float* r) {
#pragma unroll
  for (int i = 0; i < N; i++) asm volatile("" : "+f"(r[i])::"memory");
}
template <int N> __device__ __forceinline__ void clear(float* r) {
#pragma unroll
  for (int i = 0; i < N; i++) r[i] = 0.f;
  pin<N>(r);
}
template <int N> __device__ __forceinline__ void pin(uint32_t* r) {
#pragma unroll
  for (int i = 0; i < N; i++) asm volatile("" : "+r"(r[i])::"memory");
}
__device__ __forceinline__ constexpr uint64_t mkdesc(uint32_t addr, uint32_t lbo, uint32_t sbo, uint32_t swz) {
  return (uint64_t)((addr & 0x3FFFF) >> 4) | ((uint64_t)(lbo >> 4) << 16) | ((uint64_t)(sbo >> 4) << 32) | ((uint64_t)swz << 62);
}
__device__ __forceinline__ void mbar_init(uint32_t b, int c) { asm volatile("mbarrier.init.shared::cta.b64 [%0], %1;" ::"r"(b), "r"(c) : "memory"); }
__device__ __forceinline__ void mbar_expect(uint32_t b, int n) { asm volatile("mbarrier.arrive.expect_tx.shared::cta.b64 _, [%0], %1;" ::"r"(b), "r"(n) : "memory"); }
__device__ __forceinline__ void mbar_arrive(uint32_t b) { asm volatile("mbarrier.arrive.shared::cta.b64 _, [%0];" ::"r"(b) : "memory"); }
__device__ __forceinline__ bool mbar_try(uint32_t b, uint32_t ph) {
  uint32_t ok;
  asm volatile("{.reg .pred p; mbarrier.try_wait.parity.shared::cta.b64 p, [%1], %2; selp.u32 %0, 1, 0, p;}" : "=r"(ok) : "r"(b), "r"(ph) : "memory");
  return ok;
}
__device__ __forceinline__ void mbar_wait(uint32_t b, uint32_t ph) {
  if (mbar_try(b, ph)) return;
#pragma unroll 1
  for (int i = 0; i < (1 << 16); i++) {
    uint32_t ok;
    asm volatile("{.reg .pred p; mbarrier.try_wait.parity.shared::cta.b64 p, [%1], %2, 20000; selp.u32 %0, 1, 0, p;}" : "=r"(ok) : "r"(b), "r"(ph) : "memory");
    if (ok) return;
  }
  __trap();
}
__device__ __forceinline__ void bulk_load(uint32_t dst, const void* src, int bytes, uint32_t bar) {
  asm volatile("cp.async.bulk.shared::cluster.global.mbarrier::complete_tx::bytes [%0], [%1], %2, [%3];" ::"r"(dst), "l"(src), "r"(bytes), "r"(bar) : "memory");
}
__device__ __forceinline__ void tma_load(uint32_t dst, const CUtensorMap* m, int c0, int c1, uint32_t bar) {
  asm volatile("cp.async.bulk.tensor.2d.shared::cluster.global.mbarrier::complete_tx::bytes [%0], [%1, {%2, %3}], [%4];" ::"r"(dst), "l"(m), "r"(c0), "r"(c1), "r"(bar) : "memory");
}
__device__ __forceinline__ void tma_prefetch(const CUtensorMap* m, int c0, int c1) {
  asm volatile("cp.async.bulk.prefetch.tensor.2d.L2.global [%0, {%1, %2}];" ::"l"(m), "r"(c0), "r"(c1) : "memory");
}
__device__ __forceinline__ bool elect() {
  uint32_t r;
  asm volatile("{.reg .pred p; elect.sync _|p, 0xffffffff; selp.u32 %0, 1, 0, p;}" : "=r"(r));
  return r;
}
__device__ __forceinline__ void bar_sync(int id, int n) { asm volatile("bar.sync %0, %1;" ::"r"(id), "r"(n) : "memory"); }
__device__ __forceinline__ void bar_arrive(int id, int n) { asm volatile("bar.arrive %0, %1;" ::"r"(id), "r"(n) : "memory"); }
__device__ __forceinline__ bool bar_or(int id, int n, bool v) {
  uint32_t r;
  asm volatile("{.reg .pred p, q; setp.ne.u32 q, %3, 0; bar.red.or.pred p, %1, %2, q; selp.u32 %0, 1, 0, p;}" : "=r"(r) : "r"(id), "r"(n), "r"((uint32_t)v) : "memory");
  return r;
}
__device__ __forceinline__ void flag_add(int f) { asm volatile("red.release.gpu.global.add.u32 [%0], 1;" ::"l"(gFlag + f * 32) : "memory"); }
__device__ __forceinline__ void flag_wait(int f, uint32_t target, uint32_t ns) {
#pragma unroll 1
  for (int i = 0; i < (1 << 22); i++) {
    uint32_t v;
    asm volatile("ld.acquire.gpu.global.u32 %0, [%1];" : "=r"(v) : "l"(gFlag + f * 32) : "memory");
    if ((int)(v - target) >= 0) { asm volatile("fence.proxy.async.global;" ::: "memory"); return; }
    __nanosleep(ns);
  }
  __trap();
}
__device__ __forceinline__ float ex2(float x) { float y; asm("ex2.approx.ftz.f32 %0, %1;" : "=f"(y) : "f"(x)); return y; }
__device__ __forceinline__ float rcp(float x) { float y; asm("rcp.approx.ftz.f32 %0, %1;" : "=f"(y) : "f"(x)); return y; }
__device__ __forceinline__ uint32_t packbf(float lo, float hi) { uint32_t d; asm("cvt.rn.bf16x2.f32 %0, %1, %2;" : "=r"(d) : "f"(hi), "f"(lo)); return d; }
__device__ __forceinline__ float bfr(float x) { return __bfloat162float(__float2bfloat16(x)); }
__device__ __forceinline__ uint32_t hmul(uint32_t a, uint32_t b) { uint32_t d; asm("mul.rn.bf16x2 %0, %1, %2;" : "=r"(d) : "r"(a), "r"(b)); return d; }
__device__ __forceinline__ uint32_t hadd(uint32_t a, uint32_t b) { uint32_t d; asm("add.rn.bf16x2 %0, %1, %2;" : "=r"(d) : "r"(a), "r"(b)); return d; }
__device__ __forceinline__ uint32_t hsub(uint32_t a, uint32_t b) { uint32_t d; asm("sub.rn.bf16x2 %0, %1, %2;" : "=r"(d) : "r"(a), "r"(b)); return d; }
__device__ __forceinline__ void hmma(float* c, const uint4& a, uint32_t b0, uint32_t b1) {
  asm("mma.sync.aligned.m16n8k16.row.col.f32.bf16.bf16.f32 {%0,%1,%2,%3},{%4,%5,%6,%7},{%8,%9},{%0,%1,%2,%3};"
      : "+f"(c[0]), "+f"(c[1]), "+f"(c[2]), "+f"(c[3]) : "r"(a.x), "r"(a.y), "r"(a.z), "r"(a.w), "r"(b0), "r"(b1));
}
constexpr float LOG2E = 1.4426950408889634f;

__device__ __forceinline__ uint32_t exp_poly(float lo, float hi, uint32_t half2) {
  uint32_t u, mh, p;
  asm("cvt.pack.sat.s16.s32 %0, %1, %2;" : "=r"(u) : "r"(__float_as_uint(hi)), "r"(__float_as_uint(lo)));
  asm("lop3.b32 %0, %1, 0x007F007F, %2, 0xEA;" : "=r"(mh) : "r"(u), "r"(half2));
  asm("fma.rn.bf16x2 %0, %1, %2, %3;" : "=r"(p) : "r"(u), "r"(mh), "r"(u & 0xFF80FF80u));
  return p;
}
__device__ __forceinline__ void softmax64(float* s, uint32_t* p, uint32_t half2) {
  pin<32>(s);
#pragma unroll
  for (int j = 0; j < 8; j++) {
#pragma unroll
    for (int r = 0; r < 2; r++) {
      const float a = s[4 * j + 2 * r], b = s[4 * j + 2 * r + 1];
      p[2 * j + r] = ((POLYMASK >> j) & 1) ? exp_poly(a, b, half2) : packbf(ex2(a), ex2(b));
    }
  }
  pin<16>(p);
}

template <int NT> __device__ __forceinline__ void tile_max(float* s, float* m) {
  pin<4 * NT>(s);
#pragma unroll
  for (int j = 0; j < NT; j++) {
    float* mm = m + (((POLYMASK >> j) & 1) ? 0 : 2);
    mm[0] = fmaxf(mm[0], fmaxf(s[4 * j], s[4 * j + 1]));
    mm[1] = fmaxf(mm[1], fmaxf(s[4 * j + 2], s[4 * j + 3]));
  }
}
__device__ __forceinline__ float shift_of(float mpoly, float mmufu) {
  float v = fmaxf(mmufu, (mpoly * 0x1p71f) * 0x1p71f);
  v = fmaxf(v, __shfl_xor_sync(~0u, v, 1));
  v = fmaxf(v, __shfl_xor_sync(~0u, v, 2));
  return __fadd_rn(__fadd_rn(12582952.f, -v), -12582912.f);
}
__device__ __forceinline__ uint32_t shift_frag(float shift, int t) {
  const float y = shift * 0x1p-71f;
  const float r1 = y - __uint_as_float(__float_as_uint(y) & 0xFFFF0000u);
  const float r2 = r1 - __uint_as_float(__float_as_uint(r1) & 0xFFFF0000u);
  const uint32_t w0 = __byte_perm(__float_as_uint(y), __float_as_uint(r1), 0x7632), w1 = __byte_perm(__float_as_uint(r2), 0x1C000000u, 0x7632);
  const uint32_t lo = t == 0 ? w0 : w1, hi = t == 2 ? 0x1C00u : 0u;
  return t < 2 ? lo : hi;
}

struct Tile { int kind, c0, c1; };
__device__ __forceinline__ Tile tile_of(int cg, int t) {
  const int c2 = cg >> 1;
  Tile r;
  if (cg & 1) {
    if (t == 0) { r.kind = 1; r.c0 = c2 * 128; r.c1 = r.c0 + 64; }
    else { r.kind = 2; r.c0 = r.c1 = (7 * c2 + 2 + t) * 64; }
  } else {
    if (t < 2) { r.kind = 0; r.c0 = 512 + c2 * 128 + t * 64; r.c1 = r.c0 + 512; }
    else { r.kind = 2; r.c0 = r.c1 = (7 * c2 + t - 2) * 64; }
  }
  return r;
}

__global__ void __launch_bounds__(NTHREADS, 1)
fused_kernel(const __grid_constant__ CUtensorMap mQKV, const __grid_constant__ CUtensorMap mW1, const __grid_constant__ CUtensorMap mW3,
             const __grid_constant__ CUtensorMap mW2, const __grid_constant__ CUtensorMap mWO, const __grid_constant__ CUtensorMap mX,
             const bf16* __restrict__ x, bf16* __restrict__ out,
             uint64_t zero64) {
  const uint32_t zero = (uint32_t)zero64;
  extern __shared__ __align__(1024) uint8_t smem[];
  constexpr uint32_t sb = 1024;
  if ((uint32_t)__cvta_generic_to_shared(smem) != sb) __trap();
  const int tid = threadIdx.x, lane = tid & 31, g = lane >> 2, t = lane & 3;
  const int warp = __shfl_sync(~0u, tid >> 5, 0), wg = warp >> 2, w = warp & 3;
  const int b = blockIdx.x;
  const int rb = (b >> 5) * 4 + (b & 3), cg = (b >> 2) & 7;
  const int head = b >> 2, qb = b & 3;
  const int cb = b & 7;
  const int rEarly = (b >> 5) * 8 + ((0x3052 >> ((b >> 1) & 12)) & 7), rLate = (b >> 5) * 8 + ((0x6741 >> ((b >> 1) & 12)) & 7);

  if (wg < 4) TSTAMP(wg, 0);
  if (warp == 0) {
    if (elect()) {
#pragma unroll
      for (int j = 0; j < 8; j++) mbar_init(sb + B_KV + 8 * j, 1);
      asm volatile("fence.mbarrier_init.release.cluster;" ::: "memory");
#pragma unroll
      for (int j = 0; j < 8; j++) {
        mbar_expect(sb + B_KV + 8 * j, 16384);
        tma_load(sb + SM_A + j * 16384, &mX, j * 64, rb * 128, sb + B_KV + 8 * j);
      }
    }
    __syncwarp();
  }
  if (wg == 4) {
    asm volatile("setmaxnreg.dec.sync.aligned.u32 24;");
    if (w == 0) {
      TSTAMP(2, 6);
      if (elect()) {
#pragma unroll
        for (int i = 0; i < 2 * NSLOT; i++) mbar_init(sb + B_FULL1 + 8 * i, 1);
#pragma unroll
        for (int i = 0; i < NSLOT; i++) mbar_init(sb + B_EMPTY1 + 8 * i, 8);
#pragma unroll
        for (int i = 8; i < 26; i++) mbar_init(sb + B_KV + 8 * i, i < 18 ? 1 : i < 23 ? 4 : i == 23 ? 12 : i == 24 ? 1 : 8);
        asm volatile("fence.mbarrier_init.release.cluster;" ::: "memory");
      }
      __syncwarp();
      bar_arrive(1, 544);
      uint32_t epoch = 0;
      TSTAMP(2, 7);
      int slot = 0;
      uint32_t ph = 1;
#pragma unroll 1
      for (int tI = 0; tI < 5; tI++) {
        const Tile tl = tile_of(cg, tI);
        const CUtensorMap *m0 = tl.kind == 2 ? &mW1 : &mQKV, *m1 = tl.kind == 2 ? &mW3 : &mQKV;
#pragma unroll 1
        for (int k = 0; k < 8; k++) {
          const uint32_t full = sb + B_FULL1 + 8 * ((tI & 1) * NSLOT + slot), dst = sb + SM_RING + slot * 16384;
          if (tI == 4 && k == 0) {
            epoch = (epoch >> 5) + 1;
            flag_wait(F_QKV + (head >> 2), epoch * 32, 32);
            if (elect()) {
              mbar_expect(sb + B_K0, 1024);
              bulk_load(sb + SM_MERGE, gQKV + (size_t)head * HS, 1024, sb + B_K0);
            }
          }
          if (tI == 0 && k == NSLOT) {
            asm volatile("ld.relaxed.gpu.global.u32 %0, [%1];" : "=r"(epoch) : "l"(gFlag + F_O * 32) : "memory");
            const int i = 2 * NSLOT + rb + lane * 16;
            if (i < 80) {
              const Tile tp = tile_of(cg, i >> 4);
              tma_prefetch((i & 1) ? (tp.kind == 2 ? &mW3 : &mQKV) : (tp.kind == 2 ? &mW1 : &mQKV), (i & 1) ? tp.c1 : tp.c0, ((i >> 1) & 7) * 64);
            }
            __syncwarp();
          }
          mbar_wait(sb + B_EMPTY1 + 8 * slot, ph);
          if (elect()) {
            mbar_expect(full, 16384);
            tma_load(dst, m0, tl.c0, k * 64, full);
            tma_load(dst + 8192, m1, tl.c1, k * 64, full);
          }
          if (++slot == NSLOT) { slot = 0; ph ^= 1; }
        }
      }
#pragma unroll 1
      for (int j = 0; j < 8; j++) {
        if (j >= 8 - NSLOT) {
          mbar_wait(sb + B_EMPTY1 + 8 * slot, ph);
          if (++slot == NSLOT) { slot = 0; ph ^= 1; }
        }
        if (elect()) {
          mbar_expect(sb + B_KV + 8 * j, 16384);
          bulk_load(sb + SM_A + j * 16384, gQKV + (size_t)head * HS + j * 16384, 16384, sb + B_KV + 8 * j);
        }
      }
      flag_wait(F_H + rEarly, epoch * 28, 100);
      flag_wait(F_H + rLate, epoch * 28, 100);
      slot = 0; ph = 1;
#pragma unroll 1
      for (int n = 0; n < 31; n++) {
        const uint32_t full = sb + B_FULL2 + 8 * slot, dst = sb + SM_RING + slot * 24576;
        mbar_wait(sb + B_EMPTY2 + 8 * slot, ph);
        if (n < 28 && elect()) {
          mbar_expect(full, 24576);
          tma_load(dst, &mW2, cb * 64, n * 64, full);
          bulk_load(dst + 8192, gH + (size_t)(rEarly * 28 + n) * 8192, 8192, full);
          bulk_load(dst + 16384, gH + (size_t)(rLate * 28 + n) * 8192, 8192, full);
        }
        if (++slot == 3) { slot = 0; ph ^= 1; }
      }
      if (elect()) {
        mbar_expect(sb + B_WO, 65536);
#pragma unroll 1
        for (int k = 0; k < 8; k++) tma_load(sb + SM_RING + k * 8192, &mWO, cb * 64, k * 64, sb + B_WO);
      }
      flag_wait(F_O + rEarly, epoch * 32, 200);
#pragma unroll 1
      for (int n = 0; n < 8; n++) {
        mbar_wait(sb + B_OEE + 8 * (n & 1), ((n >> 1) & 1) ^ 1);
        if (elect()) {
          mbar_expect(sb + B_OE + 8 * (n & 1), 8192);
          bulk_load(sb + SM_RING + 65536 + (n & 1) * 8192, gO + (size_t)(rEarly * 8 + n) * 8192, 8192, sb + B_OE + 8 * (n & 1));
        }
      }
      mbar_wait(sb + B_ADONE, 0);
      flag_wait(F_O + rLate, epoch * 32, 20);
      if (elect()) {
#pragma unroll
        for (int i = 0; i < 4; i++) {
          mbar_expect(sb + B_O + 8 * i, 16384);
          bulk_load(sb + SM_A + i * 16384, gO + (size_t)rLate * 65536 + i * 16384, 16384, sb + B_O + 8 * i);
        }
      }
    } else {
      if (w < 3) {
#pragma unroll 1
        for (int tI = w - 1; tI < 5; tI += 2) {
          const Tile tl = tile_of(cg, tI);
          bar_sync(3 + w, 288);
          if (lane < (tl.kind ? 2 : 1)) flag_add(tl.kind == 2 ? F_H + rb * 2 + lane : F_QKV + ((tl.c0 >> 6) & 7) + lane);
          __syncwarp();
        }
      }
#pragma unroll 1
      for (int i = 0; i < (w == 2 ? 2 : 3); i++) {
        bar_sync(12 + w, 160);
        if (lane == 0) flag_add(F_O + qb * 8 + (((w == 1 ? 0x102 : w == 2 ? 0x43 : 0x765) >> (i * 4)) & 7));
        __syncwarp();
      }
    }
    return;
  }

  asm volatile("setmaxnreg.inc.sync.aligned.u32 112;");

  {
    if (tid < 128) ((uint32_t*)(smem + SM_ONES))[tid] = 0x3F803F80u;
    {
      const int n = tid >> 3, k = (tid & 7) * 2;
      const bool poly = (POLYMASK >> (n >> 3)) & 1;
      const float cm = -127.f + 0.5849625f - 0.0020f, chi = bfr(cm), clo = cm - chi, sc = poly ? 0x1p-71f : 0x1p71f;
      float v0 = 0.f, v1 = 0.f;
      if (k == 0) { v0 = sc; v1 = sc; }
      if (k == 2) { v0 = sc; v1 = poly ? 0.f : chi * sc; }
      if (k == 4) { v0 = poly ? 0.f : clo * sc; }
      *(uint32_t*)(smem + SM_BIAS + n * 32 + (((k >> 3) ^ ((n >> 2) & 1)) << 4) + (k & 7) * 2) = packbf(v0, v1);
    }
    float cs[4] = {0.f, 0.f, 0.f, 0.f}, ca[4] = {0.f, 0.f, 0.f, 0.f}, cb[4] = {0.f, 0.f, 0.f, 0.f};
    uint4 xv[16];
    const int row = warp * 8 + g;
    uint8_t* xs = smem + SM_A + row * 128;
    const int xo0 = (((4 * (g & 1) + t) ^ g) << 4), xo1 = xo0 ^ 64;
    bar_sync(2, 512);
#pragma unroll
    for (int j = 0; j < 16; j++) {
      if ((j & 1) == 0) mbar_wait(sb + B_KV + 4 * j, 0);
      if (j == 0 && wg == 3) TSTAMP(3, 7);
      if (j == 8 && wg == 3) TSTAMP(3, 13);
      if (j == 14 && wg == 3) TSTAMP(3, 14);
      xv[j] = *(const uint4*)(xs + (j >> 1) * 16384 + ((j & 1) ? xo1 : xo0));
      hmma(cs, xv[j], 0x3F803F80u, 0x3F803F80u);
      hmma(ca, xv[j], xv[j].x, xv[j].z);
      hmma(cb, xv[j], xv[j].y, xv[j].w);
    }
    const float mean = (cs[0] + cs[2]) * (1.f / DM);
    const uint32_t m2 = packbf(mean, mean);

#pragma unroll
    for (int j = 0; j < 16; j++)
      *(uint4*)(xs + (j >> 1) * 16384 + ((j & 1) ? xo1 : xo0)) = make_uint4(hsub(xv[j].x, m2), hsub(xv[j].y, m2), hsub(xv[j].z, m2), hsub(xv[j].w, m2));
    {
      const float var = fmaxf(((g & 1) ? ca[1] + cb[3] : ca[0] + cb[2]) * (1.f / DM) - mean * mean, 0.f);
      float sd;
      asm("sqrt.approx.f32 %0, %1;" : "=f"(sd) : "f"(bfr(bfr(var) + 1e-5f)));
      if (t == (g >> 1)) ((float*)(smem + SM_RSTD))[row] = rcp(bfr(sd));
    }

    asm volatile("fence.proxy.async.shared::cta;" ::: "memory");
    bar_sync(1, 544);
  }
  TSTAMP(wg, 1);
  const int pair = wg >> 1, half = wg & 1;

  const uint8_t* qbase = gQKV + (uint32_t)(head * HS + 131072 + (qb * 512 + w * 16 + g) * 32 + t * 4);
  auto load_q = [&](uint32_t* q, int rbl) {
    const uint32_t* qp = (const uint32_t*)(qbase + rbl * 2048);
    q[0] = __ldcg(qp); q[1] = __ldcg(qp + 64); q[2] = __ldcg(qp + 4); q[3] = __ldcg(qp + 68);
  };
  uint32_t q4[16];
  {
    const uint64_t dA0 = (mkdesc(sb + SM_A, 16, 1024, 1) ^ zero64) + half * 512, dB0 = mkdesc(sb + SM_RING, 8192, 1024, 1) ^ zero64;
    const bool lead = elect();
#pragma unroll 1
    for (int tI = pair; tI < 5; tI += 2) {
      float acc[64];
      const uint32_t par = (uint32_t)(PARITY1 >> (tI * 8)), slots = (uint32_t)(0x432104321043210ull >> (((tI * 3) % NSLOT) * 4));
      if (tI > 0) bar_sync(6 + pair, 512);
#pragma unroll
      for (int k = 0; k < 8; k++) {
        const uint32_t slot = (slots >> (4 * k)) & 7;
        mbar_wait(sb + B_FULL1 + 8 * NSLOT * pair + 8 * slot, par >> k);
        if (tI == 1 && wg == 2) TSTAMP(4, 8 + k);
        const uint64_t dA = dA0 + k * 1024, dB = dB0 + slot * 1024;
        wg_fence();
        if (k == 0) wg_ss_n128<1, 0>(acc, dA, dB); else wg_ss_n128<1, 1>(acc, dA, dB);
        wg_ss_n128<1, 1>(acc, dA + 2, dB + 128);
        wg_ss_n128<1, 1>(acc, dA + 4, dB + 256);
        wg_ss_n128<1, 1>(acc, dA + 6, dB + 384);
        wg_commit();
        if (k == 7 && tI < 4) bar_arrive(7 - pair, 512);
        if (k > 0) {
          wg_wait<1>();
          if (lead) mbar_arrive(sb + B_EMPTY1 + 8 * ((slots >> (4 * k - 4)) & 7));
        }
      }
      wg_wait<0>();
      if (lead) mbar_arrive(sb + B_EMPTY1 + 8 * (slots >> 28));
      pin<64>(acc);
      TSTAMP(wg, 2 + (tI >> 1) * 2);
      if (tI == 3) {
        mbar_wait(sb + B_K0, 0);
#pragma unroll
        for (int i = 0; i < 4; i++) load_q(q4 + 4 * i, half * 4 + i);
      }
      const Tile tl = tile_of(cg, tI);
      const int lrow = half * 64 + w * 16 + g;
      const float r0 = ((const float*)(smem + SM_RSTD))[lrow], r1 = ((const float*)(smem + SM_RSTD))[lrow + 8];
      if (tl.kind == 2) {
        uint32_t* hp = (uint32_t*)(gH + (size_t)((rb * 2 + half) * 28 + (tl.c0 >> 6)) * 8192 + w * 256) + lane;
#pragma unroll
        for (int j = 0; j < 8; j++) {
#pragma unroll
          for (int r = 0; r < 2; r++) {
            const float rs = r ? r1 : r0, e = -LOG2E * rs, q = rs * rs;
            const float g0 = acc[4 * j + 2 * r], g1 = acc[4 * j + 2 * r + 1];
            const float h0 = (g0 * q) * acc[32 + 4 * j + 2 * r] * rcp(1.f + ex2(g0 * e));
            const float h1 = (g1 * q) * acc[33 + 4 * j + 2 * r] * rcp(1.f + ex2(g1 * e));
            hp[j * 256 + r * 32] = packbf(h0, h1);
          }
        }
      } else {
        const bool isq = tl.kind == 1;
        uint8_t* p0 = gQKV + (uint32_t)(((tl.c0 >> 6) & 7) * 4 * HS + lrow * 32 + (isq ? 131072 + rb * 4096 + t * 8 : rb * 8192 + ((t * 8) ^ ((g & 4) << 2))));
        uint8_t* p1 = p0 + (isq ? 4 * HS : 4096);
        constexpr float QS = 0.25f * LOG2E * 0x1p-71f;
        const float k0 = ((POLYMASK >> (2 * w)) & 1) ? 0x1p-71f : 0x1p71f, k1 = ((POLYMASK >> (2 * w + 1)) & 1) ? 0x1p-71f : 0x1p71f;
        const float sc[4] = {r0 * (isq ? QS : k0), r1 * (isq ? QS : k1), r0 * (isq ? QS : 1.f), r1 * (isq ? QS : 1.f)};
#pragma unroll
        for (int i = 0; i < 16; i++) {
          const float* a = acc + (i >> 1) * 8 + 2 * (i & 1);
          const float f = sc[(i >> 3) * 2 + (i & 1)];
          *(uint2*)((i < 8 ? p0 : p1) + ((i >> 1) & 3) * HS + (i & 1) * 256) = make_uint2(packbf(a[0] * f, a[1] * f), packbf(a[4] * f, a[5] * f));
        }
      }
      bar_arrive(4 + pair, 288);
      TSTAMP(wg, 3 + (tI >> 1) * 2);
    }
  }

  if (pair == 1) {
    float s[64];
    wg_fence();
#pragma unroll
    for (int i = 0; i < 4; i++) wg_rs_n32<0, 0>(s + 16 * i, q4 + 4 * i, mkdesc(sb + SM_MERGE, 16, 256, 3));
    wg_commit();
    wg_wait<0>();
#pragma unroll
    for (int i = 0; i < 4; i++) {
      float m[4] = {-INFINITY, -INFINITY, -INFINITY, -INFINITY};
      tile_max<4>(s + 16 * i, m);
      const float s0 = shift_of(m[0], m[2]), s1 = shift_of(m[1], m[3]);
      if (t < 2) ((float*)(smem + SM_SHIFT))[(half * 4 + i) * 64 + w * 16 + t * 8 + g] = t ? s1 : s0;
    }
    __syncwarp();
    if (lane == 0) mbar_arrive(sb + B_SHIFT);
    TSTAMP(wg, 15);
  }

  if (wg < 3) {
    asm volatile("setmaxnreg.inc.sync.aligned.u32 120;");
    constexpr uint64_t VS = (uint64_t)(32 - (32LL << 16));
    const uint32_t half2 = 0x3F003F00u + zero;
    const uint64_t dBias = mkdesc(sb + SM_BIAS, 16, 256, 3) ^ zero64;
    const uint64_t dV0 = mkdesc(sb + SM_A + 4096, SM_ONES - SM_A - 4096, 256, 3);
    const float* shifts = (const float*)(smem + SM_SHIFT) + w * 16 + g;
#define SEG(r, c0, cl, mode) (uint64_t)((r) | (c0) << 3 | (cl) << 7 | (mode) << 11 | 1 << 13)
    uint64_t segs = wg == 0   ? SEG(2, 5, 15, 2) | SEG(0, 0, 15, 0) << 16 | SEG(1, 0, 15, 0) << 32
                    : wg == 1 ? SEG(2, 0, 4, 1) | SEG(5, 11, 15, 1) << 16 | SEG(3, 0, 15, 0) << 32 | SEG(4, 0, 15, 0) << 48
                              : SEG(5, 0, 10, 2) | SEG(6, 0, 15, 0) << 16 | SEG(7, 0, 15, 0) << 32;
    uint32_t q[4], qa[4], p0[16], p1[16];
    float s[32], o[12], shift[2];
    clear<32>(s);
    int ready = wg == 0 ? 2 : 0;
    mbar_wait(sb + B_SHIFT, 0);
    load_q(q, segs & 7);
    shift[0] = shifts[(segs & 7) * 64];
    shift[1] = shifts[(segs & 7) * 64 + 8];
    qa[2] = zero & q[0];
    qa[3] = zero & q[1];
    mbar_wait(sb + B_KV + 8 * ready, 1);
    TSTAMP(wg, 8);
    bool exact = false;
    bool primed = false;
#pragma unroll 1
    while (true) {
      const uint32_t sg = (uint32_t)segs, sn = sg >> 16;
      const int rbl = sg & 7, c0 = (sg >> 3) & 15, cl = (sg >> 7) & 15, mode = (sg >> 11) & 3;
      uint64_t c = dV0 + (uint64_t)c0 * (16 * VS);
      if (!primed) {
        if (exact) {
          load_q(q, rbl);
          float m[4] = {-INFINITY, -INFINITY, -INFINITY, -INFINITY};
#pragma unroll 1
          for (int i = 2 * c0; i < 2 * cl + 2; i++) {
            wg_fence();
            wg_rs_n64<0, 2>(s, q, dV0 - 256 + (i >> 1) * 512 + (i & 1) * 128);
            wg_commit();
            wg_wait<0>();
            tile_max<8>(s, m);
          }
          shift[0] = shift_of(m[0], m[2]);
          shift[1] = shift_of(m[1], m[3]);
        }
        qa[0] = shift_frag(shift[0], t);
        qa[1] = shift_frag(shift[1], t);
        wg_fence();
        wg_rs_n64<0, 2>(s, qa, dBias);
        wg_rs_n64<0, 1>(s, q, c - 256);
        wg_commit();
        wg_wait<0>();
      }
      uint32_t qn[4];
      load_q(qn, sn & 7);
      clear<12>(o);
      auto first_half = [&]() {
        softmax64(s, p0, half2);
        wg_fence();
        wg_rs_n64<0, 2>(s, qa, dBias);
        wg_rs_n64<0, 1>(s, q, c - 128);
        wg_commit();
#pragma unroll
        for (int k = 0; k < 4; k++) wg_rs_n24<1, 1>(o, p0 + 4 * k, c + k * VS);
        wg_commit();
        wg_wait<1>();
        softmax64(s, p1, half2);
      };
      auto second_half = [&](uint64_t dKnext) {
        wg_fence();
        wg_rs_n64<0, 2>(s, qa, dBias);
        wg_rs_n64<0, 1>(s, q, dKnext);
        wg_commit();
#pragma unroll
        for (int k = 0; k < 4; k++) wg_rs_n24<1, 1>(o, p1 + 4 * k, c + (4 + k) * VS);
        wg_commit();
      };
#pragma unroll 1
      for (int ci = c0; ci < cl;) {
        if (ready < 7) mbar_wait(sb + B_KV + 8 * ++ready, 1);
        ci = ready >= 7 ? cl : min(cl, 2 * ready);
        const uint32_t cend = (uint32_t)dV0 + ci * (uint32_t)(16 * VS);
#pragma unroll 1
        do {
          first_half();
          second_half(c + 256);
          c += 16 * VS;
          wg_wait<1>();
        } while ((uint32_t)c != cend);
      }
      if (ready < 8) {
#pragma unroll 1
        for (int j = 0; j < 8; j++) mbar_wait(sb + B_KV + 8 * j, 1);
        ready = 8;
      }
      const float bias[2] = {shift[0], shift[1]};
      shift[0] = shifts[(sn & 7) * 64];
      shift[1] = shifts[(sn & 7) * 64 + 8];
      first_half();
      qa[0] = shift_frag(shift[0], t);
      qa[1] = shift_frag(shift[1], t);
#pragma unroll
      for (int i = 0; i < 4; i++) q[i] = qn[i];
      pin<4>(q);
      pin<2>(qa);
      second_half(dV0 - 256 + ((sn >> 3) & 15) * 512);
      wg_wait<0>();
      pin<12>(o);
      exact = __all_sync(~0u, bar_or(10 + wg, 128, !exact && !(o[8] < 0x1p100f && o[10] < 0x1p100f)));
      primed = !exact;
      if (exact) continue;
      segs >>= 16;
      if (mode == 1) {
        float* mp = (float*)(smem + SM_MERGE + (rbl >> 2) * 6144) + (tid & 127);
        o[9] = bias[0]; o[11] = bias[1];
#pragma unroll
        for (int i = 0; i < 12; i++) mp[i * 128] = o[i];
        bar_arrive(8 + (rbl >> 2), 256);
        continue;
      }
      if (mode == 2) {
        const float* mp = (const float*)(smem + SM_MERGE + (wg >> 1) * 6144) + (tid & 127);
        bar_sync(8 + (wg >> 1), 256);
#pragma unroll
        for (int r = 0; r < 2; r++) {
          const float bo = mp[(9 + 2 * r) * 128], bm = fminf(bo, bias[r]);
          const float fa = ex2(0.5f * (bm - bias[r])), fb = ex2(0.5f * (bm - bo));
          o[2 * r] = o[2 * r] * fa * fa + mp[(2 * r) * 128] * fb * fb;
          o[2 * r + 1] = o[2 * r + 1] * fa * fa + mp[(2 * r + 1) * 128] * fb * fb;
          o[4 + 2 * r] = o[4 + 2 * r] * fa * fa + mp[(4 + 2 * r) * 128] * fb * fb;
          o[5 + 2 * r] = o[5 + 2 * r] * fa * fa + mp[(5 + 2 * r) * 128] * fb * fb;
          o[8 + 2 * r] = o[8 + 2 * r] * fa * fa + mp[(8 + 2 * r) * 128] * fb * fb;
        }
      }
      if (sn == 0 && lane == 0) mbar_arrive(sb + B_ADONE);
#pragma unroll
      for (int r = 0; r < 2; r++) {
        const float inv = rcp(o[8 + 2 * r]);
        const uint32_t a = packbf(o[2 * r] * inv, o[2 * r + 1] * inv), d = packbf(o[4 + 2 * r] * inv, o[5 + 2 * r] * inv);
        const uint32_t e = __shfl_xor_sync(~0u, (t & 2) ? a : d, 2);
        *(uint2*)(gO + (size_t)((qb * 8 + rbl) * 8 + (head >> 2)) * 8192 + ((head & 3) * 2 + (t & 1)) * 1024 + (2 * w + r) * 128 + g * 16 + (t & 2) * 4) =
            (t & 2) ? make_uint2(e, d) : make_uint2(a, e);
      }
      bar_arrive(13 + wg, 160);
      TSTAMP(wg, sn == 0 ? 11 : mode ? 9 : 10);
      if (sn == 0) break;
    }
  } else {
    asm volatile("setmaxnreg.dec.sync.aligned.u32 96;");
    uint32_t gate[32];
    const uint64_t dB0 = mkdesc(sb + SM_RING, 8192, 1024, 1) ^ zero64;
    {
      const uint64_t dA0 = mkdesc(sb + SM_RING + 8192, 1024, 128, 0) ^ zero64;
      float acc[64];
      clear<64>(acc);
      int slot = 0;
      uint32_t ph = 0;
#pragma unroll 1
      for (int n = 0; n < 28; n++) {
        mbar_wait(sb + B_FULL2 + 8 * slot, ph);
        const uint64_t dA = dA0 + slot * 1536, dB = dB0 + slot * 1536;
        wg_fence();
#pragma unroll
        for (int k = 0; k < 4; k++) {
          wg_ss_n64<1, 1>(acc, dA + k * 128, dB + k * 128);
          wg_ss_n64<1, 1>(acc + 32, dA + 512 + k * 128, dB + k * 128);
        }
        wg_commit();
        wg_wait<0>();
        if (lane == 0) mbar_arrive(sb + B_EMPTY2 + 8 * slot);
        if (++slot == 3) { slot = 0; ph ^= 1; }
      }
      pin<64>(acc);
#pragma unroll
      for (int i = 0; i < 32; i++) {
        const uint32_t f = packbf(acc[2 * i], acc[2 * i + 1]);
        const float f0 = __uint_as_float(f << 16), f1 = __uint_as_float(f & 0xFFFF0000u);
        gate[i] = packbf(f0 * rcp(1.f + ex2(-LOG2E * f0)), f1 * rcp(1.f + ex2(-LOG2E * f1)));
      }
      mbar_wait(sb + B_WO, 0);
    }
    TSTAMP(wg, 8);
#pragma unroll
    for (int pass = 0; pass < 2; pass++) {
      const size_t off = (size_t)((pass ? rLate : rEarly) * 64 + w * 16 + g) * DM + cb * 64 + (t & 1) * 8 + (t & 2) * 2;
      uint2 xr[8];
#pragma unroll
      for (int i = 0; i < 8; i++) xr[i] = __ldg((const uint2*)(x + off + (i & 1) * 8 * DM + (i >> 1) * 16));
      float acc[32];
      clear<32>(acc);
      if (pass == 0) {
        const uint64_t dA0 = mkdesc(sb + SM_RING + 65536, 1024, 128, 0) ^ zero64;
#pragma unroll 1
        for (int n = 0; n < 8; n++) {
          mbar_wait(sb + B_OE + 8 * (n & 1), (n >> 1) & 1);
          wg_fence();
#pragma unroll
          for (int k = 0; k < 4; k++) wg_ss_n64<1, 1>(acc, dA0 + (n & 1) * 512 + k * 128, dB0 + n * 512 + k * 128);
          wg_commit();
          wg_wait<0>();
          if (lane == 0) mbar_arrive(sb + B_OEE + 8 * (n & 1));
        }
      } else {
        mbar_wait(sb + B_ADONE, 0);
        const uint64_t dA = mkdesc(sb + SM_A, 1024, 128, 0) ^ zero64;
#pragma unroll 1
        for (int n = 0; n < 4; n++) {
          mbar_wait(sb + B_O + 8 * n, 0);
          wg_fence();
#pragma unroll
          for (int k = 0; k < 8; k++) wg_ss_n64<1, 1>(acc, dA + (n * 8 + k) * 128, dB0 + (n * 8 + k) * 128);
          wg_commit();
        }
        wg_wait<0>();
      }
      pin<32>(acc);
      TSTAMP(wg, 9 + 2 * pass);
#pragma unroll
      for (int i = 0; i < 8; i++) {
        const int ia = (i >> 1) * 4 + (i & 1), ib = ia + 2;
        const uint32_t ya = hmul(packbf(acc[2 * ia], acc[2 * ia + 1]), gate[pass * 16 + ia]);
        const uint32_t yb = hmul(packbf(acc[2 * ib], acc[2 * ib + 1]), gate[pass * 16 + ib]);
        const uint32_t e = __shfl_xor_sync(~0u, (t & 1) ? ya : yb, 1);
        const uint32_t lo = (t & 1) ? e : ya, hi = (t & 1) ? yb : e;
        *(uint2*)(out + off + (i & 1) * 8 * DM + (i >> 1) * 16) = make_uint2(hadd(xr[i].x, lo), hadd(xr[i].y, hi));
      }
      TSTAMP(wg, 10 + 2 * pass);
    }
  }
}

typedef CUresult (*EncodeFn)(CUtensorMap*, CUtensorMapDataType, cuuint32_t, void*, const cuuint64_t*, const cuuint64_t*, const cuuint32_t*,
                             const cuuint32_t*, CUtensorMapInterleave, CUtensorMapSwizzle, CUtensorMapL2promotion, CUtensorMapFloatOOBfill);

void make_map(EncodeFn enc, CUtensorMap* m, void* p, int rows, int cols, int boxrows = 64) {
  const cuuint64_t dims[2] = {(cuuint64_t)cols, (cuuint64_t)rows}, strides[1] = {(cuuint64_t)cols * 2};
  const cuuint32_t box[2] = {64, (cuuint32_t)boxrows}, es[2] = {1, 1};
  enc(m, CU_TENSOR_MAP_DATA_TYPE_BFLOAT16, 2, p, dims, strides, box, es, CU_TENSOR_MAP_INTERLEAVE_NONE, CU_TENSOR_MAP_SWIZZLE_128B,
      CU_TENSOR_MAP_L2_PROMOTION_L2_128B, CU_TENSOR_MAP_FLOAT_OOB_FILL_NONE);
}

}

extern "C" void kernel_launch(void* const* d_in, const int* in_sizes, int n_in, void* d_out, int out_size) {
  (void)in_sizes; (void)n_in; (void)out_size;
  void* fn = nullptr;
  cudaDriverEntryPointQueryResult qr;
  cudaGetDriverEntryPoint("cuTensorMapEncodeTiled", &fn, cudaEnableDefault, &qr);
  EncodeFn enc = (EncodeFn)fn;
  CUtensorMap mQKV, mW1, mW3, mW2, mWO, mX;
  make_map(enc, &mX, d_in[0], SEQ, DM, 128);
  make_map(enc, &mQKV, d_in[1], DM, 3 * DM);
  make_map(enc, &mWO, d_in[2], DM, DM);
  make_map(enc, &mW1, d_in[4], DM, FF);
  make_map(enc, &mW3, d_in[5], DM, FF);
  make_map(enc, &mW2, d_in[6], FF, DM);
  cudaFuncSetAttribute(fused_kernel, cudaFuncAttributeMaxDynamicSharedMemorySize, SM_TOTAL);
  fused_kernel<<<128, NTHREADS, SM_TOTAL>>>(mQKV, mW1, mW3, mW2, mWO, mX, (const bf16*)d_in[0], (bf16*)d_out, 0ull);
}
```

```cpp
#include <cuda_runtime.h>
#include <cuda_bf16.h>
#include <cuda.h>
#include <stdint.h>

namespace {

typedef __nv_bfloat16 bf16;
constexpr int SEQ = 2048, DM = 512, FF = 1792;
constexpr int NTHREADS = 640;
constexpr int NSLOT = 5;
constexpr uint64_t PARITY1 = 0xaa6c6ce0e0ull;
#define S2 11
#define S5 11
constexpr int SPLIT2 = S2, SPLIT5 = S5;
#define KV1 4
#define NT1 4
#define PACE 60
#define PACEN 2
#define NHC 4
#define HANDJ 31
#define FJ 22
#define TDBG 1
#define XL 2
#define PFS 7
#define BGATE 3
#define BFREE 1
#define TAILA 1
#define TAILE 1
#define TSLEEP 0
#define PM 0x1F
constexpr int NSH = (5 - NT1) * 16;
constexpr uint32_t POLYMASK = PM;

constexpr uint32_t SM_A     = 0;
constexpr uint32_t SM_RING  = 131072;
constexpr uint32_t SM_GATE  = SM_RING + 65536;
constexpr uint32_t SM_ONES  = SM_RING + 81920;
constexpr uint32_t SM_MERGE = SM_ONES + 512;
constexpr uint32_t SM_RSTD  = SM_MERGE + 8192;
constexpr uint32_t SM_MEAN  = SM_RSTD + 512;
constexpr uint32_t SM_SHIFT = SM_MERGE + 12288;
constexpr uint32_t SM_BIAS  = SM_SHIFT + 4096;
constexpr uint32_t SM_ZERO  = SM_BIAS + 2048;
constexpr uint32_t SM_FAIL  = SM_ZERO + 48;
constexpr uint32_t B_X      = SM_ZERO + 56;
constexpr uint32_t B_FULL1  = B_X + 64;
constexpr uint32_t B_FULL2  = B_FULL1 + 16 * NSLOT;
constexpr uint32_t B_WO     = B_FULL2 + 24;
constexpr uint32_t B_K0     = B_WO + 8;
constexpr uint32_t B_OE     = B_K0 + 8;
constexpr uint32_t B_HP     = B_OE + 8;
constexpr uint32_t B_EMPTY1 = B_HP + 8;
constexpr uint32_t B_SHIFT  = B_EMPTY1 + 8 * NSLOT;
constexpr uint32_t B_KV     = B_SHIFT + 8;
constexpr uint32_t B_EMPTY2 = B_KV + 16;
constexpr uint32_t B_TAKEN  = B_EMPTY2 + 24;
constexpr uint32_t SM_TOTAL = B_TAKEN + 8;
static_assert(SM_TOTAL <= 232448, "shared memory");

constexpr int HS = 196608;
__device__ __align__(1024) uint8_t gQKV[32 * HS];
__device__ __align__(1024) uint8_t gH[16 * 28 * 16384];
__device__ __align__(1024) uint4 gO[32 * 32 * 128];
__device__ __align__(1024) uint8_t gD[16 * 131072];
__device__ __align__(1024) uint8_t gP[128 * 5120];
__device__ uint32_t gFlag[200 * 32];
constexpr int F_QKV = 0, F_H = 8, F_D = 24, F_O = 40, F_P = 72;
__device__ __forceinline__ int pair_slot(int r64) { return (r64 & ~7) + ((0x56237014 >> ((r64 & 7) * 4)) & 7); }
#define CSTAMP()
#define TSTAMP(role, i)

template<int TB, int SD> __device__ __forceinline__ void wg_rs_n24(float* d, const uint32_t* a, uint64_t db) {
  if (SD)
    asm volatile("wgmma.mma_async.sync.aligned.m64n24k16.f32.bf16.bf16 {%0,%1,%2,%3,%4,%5,%6,%7,%8,%9,%10,%11}, {%12,%13,%14,%15}, %16, %18, 1, 1, %17;"
      : "+f"(d[0]),"+f"(d[1]),"+f"(d[2]),"+f"(d[3]),"+f"(d[4]),"+f"(d[5]),"+f"(d[6]),"+f"(d[7]),"+f"(d[8]),"+f"(d[9]),"+f"(d[10]),"+f"(d[11])
      : "r"(a[0]), "r"(a[1]), "r"(a[2]), "r"(a[3]), "l"(db), "n"(TB), "n"(SD & 1));
  else
    asm volatile("wgmma.mma_async.sync.aligned.m64n24k16.f32.bf16.bf16 {%0,%1,%2,%3,%4,%5,%6,%7,%8,%9,%10,%11}, {%12,%13,%14,%15}, %16, 0, 1, 1, %17;"
      : "=f"(d[0]),"=f"(d[1]),"=f"(d[2]),"=f"(d[3]),"=f"(d[4]),"=f"(d[5]),"=f"(d[6]),"=f"(d[7]),"=f"(d[8]),"=f"(d[9]),"=f"(d[10]),"=f"(d[11])
      : "r"(a[0]), "r"(a[1]), "r"(a[2]), "r"(a[3]), "l"(db), "n"(TB));
}
template<int TB, int SD> __device__ __forceinline__ void wg_rs_n32(float* d, const uint32_t* a, uint64_t db) {
  if (SD)
    asm volatile("wgmma.mma_async.sync.aligned.m64n32k16.f32.bf16.bf16 {%0,%1,%2,%3,%4,%5,%6,%7,%8,%9,%10,%11,%12,%13,%14,%15}, {%16,%17,%18,%19}, %20, %22, 1, 1, %21;"
      : "+f"(d[0]),"+f"(d[1]),"+f"(d[2]),"+f"(d[3]),"+f"(d[4]),"+f"(d[5]),"+f"(d[6]),"+f"(d[7]),"+f"(d[8]),"+f"(d[9]),"+f"(d[10]),"+f"(d[11]),"+f"(d[12]),"+f"(d[13]),"+f"(d[14]),"+f"(d[15])
      : "r"(a[0]), "r"(a[1]), "r"(a[2]), "r"(a[3]), "l"(db), "n"(TB), "n"(SD & 1));
  else
    asm volatile("wgmma.mma_async.sync.aligned.m64n32k16.f32.bf16.bf16 {%0,%1,%2,%3,%4,%5,%6,%7,%8,%9,%10,%11,%12,%13,%14,%15}, {%16,%17,%18,%19}, %20, 0, 1, 1, %21;"
      : "=f"(d[0]),"=f"(d[1]),"=f"(d[2]),"=f"(d[3]),"=f"(d[4]),"=f"(d[5]),"=f"(d[6]),"=f"(d[7]),"=f"(d[8]),"=f"(d[9]),"=f"(d[10]),"=f"(d[11]),"=f"(d[12]),"=f"(d[13]),"=f"(d[14]),"=f"(d[15])
      : "r"(a[0]), "r"(a[1]), "r"(a[2]), "r"(a[3]), "l"(db), "n"(TB));
}
template<int TB, int SD> __device__ __forceinline__ void wg_rs_n64(float* d, const uint32_t* a, uint64_t db) {
  if (SD)
    asm volatile("wgmma.mma_async.sync.aligned.m64n64k16.f32.bf16.bf16 {%0,%1,%2,%3,%4,%5,%6,%7,%8,%9,%10,%11,%12,%13,%14,%15,%16,%17,%18,%19,%20,%21,%22,%23,%24,%25,%26,%27,%28,%29,%30,%31}, {%32,%33,%34,%35}, %36, %38, 1, 1, %37;"
      : "+f"(d[0]),"+f"(d[1]),"+f"(d[2]),"+f"(d[3]),"+f"(d[4]),"+f"(d[5]),"+f"(d[6]),"+f"(d[7]),"+f"(d[8]),"+f"(d[9]),"+f"(d[10]),"+f"(d[11]),"+f"(d[12]),"+f"(d[13]),"+f"(d[14]),"+f"(d[15]),"+f"(d[16]),"+f"(d[17]),"+f"(d[18]),"+f"(d[19]),"+f"(d[20]),"+f"(d[21]),"+f"(d[22]),"+f"(d[23]),"+f"(d[24]),"+f"(d[25]),"+f"(d[26]),"+f"(d[27]),"+f"(d[28]),"+f"(d[29]),"+f"(d[30]),"+f"(d[31])
      : "r"(a[0]), "r"(a[1]), "r"(a[2]), "r"(a[3]), "l"(db), "n"(TB), "n"(SD & 1));
  else
    asm volatile("wgmma.mma_async.sync.aligned.m64n64k16.f32.bf16.bf16 {%0,%1,%2,%3,%4,%5,%6,%7,%8,%9,%10,%11,%12,%13,%14,%15,%16,%17,%18,%19,%20,%21,%22,%23,%24,%25,%26,%27,%28,%29,%30,%31}, {%32,%33,%34,%35}, %36, 0, 1, 1, %37;"
      : "=f"(d[0]),"=f"(d[1]),"=f"(d[2]),"=f"(d[3]),"=f"(d[4]),"=f"(d[5]),"=f"(d[6]),"=f"(d[7]),"=f"(d[8]),"=f"(d[9]),"=f"(d[10]),"=f"(d[11]),"=f"(d[12]),"=f"(d[13]),"=f"(d[14]),"=f"(d[15]),"=f"(d[16]),"=f"(d[17]),"=f"(d[18]),"=f"(d[19]),"=f"(d[20]),"=f"(d[21]),"=f"(d[22]),"=f"(d[23]),"=f"(d[24]),"=f"(d[25]),"=f"(d[26]),"=f"(d[27]),"=f"(d[28]),"=f"(d[29]),"=f"(d[30]),"=f"(d[31])
      : "r"(a[0]), "r"(a[1]), "r"(a[2]), "r"(a[3]), "l"(db), "n"(TB));
}
template<int TB, int SD> __device__ __forceinline__ void wg_rs_n128(float* d, const uint32_t* a, uint64_t db) {
  if (SD)
    asm volatile("wgmma.mma_async.sync.aligned.m64n128k16.f32.bf16.bf16 {%0,%1,%2,%3,%4,%5,%6,%7,%8,%9,%10,%11,%12,%13,%14,%15,%16,%17,%18,%19,%20,%21,%22,%23,%24,%25,%26,%27,%28,%29,%30,%31,%32,%33,%34,%35,%36,%37,%38,%39,%40,%41,%42,%43,%44,%45,%46,%47,%48,%49,%50,%51,%52,%53,%54,%55,%56,%57,%58,%59,%60,%61,%62,%63}, {%64,%65,%66,%67}, %68, %70, 1, 1, %69;"
      : "+f"(d[0]),"+f"(d[1]),"+f"(d[2]),"+f"(d[3]),"+f"(d[4]),"+f"(d[5]),"+f"(d[6]),"+f"(d[7]),"+f"(d[8]),"+f"(d[9]),"+f"(d[10]),"+f"(d[11]),"+f"(d[12]),"+f"(d[13]),"+f"(d[14]),"+f"(d[15]),"+f"(d[16]),"+f"(d[17]),"+f"(d[18]),"+f"(d[19]),"+f"(d[20]),"+f"(d[21]),"+f"(d[22]),"+f"(d[23]),"+f"(d[24]),"+f"(d[25]),"+f"(d[26]),"+f"(d[27]),"+f"(d[28]),"+f"(d[29]),"+f"(d[30]),"+f"(d[31]),"+f"(d[32]),"+f"(d[33]),"+f"(d[34]),"+f"(d[35]),"+f"(d[36]),"+f"(d[37]),"+f"(d[38]),"+f"(d[39]),"+f"(d[40]),"+f"(d[41]),"+f"(d[42]),"+f"(d[43]),"+f"(d[44]),"+f"(d[45]),"+f"(d[46]),"+f"(d[47]),"+f"(d[48]),"+f"(d[49]),"+f"(d[50]),"+f"(d[51]),"+f"(d[52]),"+f"(d[53]),"+f"(d[54]),"+f"(d[55]),"+f"(d[56]),"+f"(d[57]),"+f"(d[58]),"+f"(d[59]),"+f"(d[60]),"+f"(d[61]),"+f"(d[62]),"+f"(d[63])
      : "r"(a[0]), "r"(a[1]), "r"(a[2]), "r"(a[3]), "l"(db), "n"(TB), "n"(SD & 1));
  else
    asm volatile("wgmma.mma_async.sync.aligned.m64n128k16.f32.bf16.bf16 {%0,%1,%2,%3,%4,%5,%6,%7,%8,%9,%10,%11,%12,%13,%14,%15,%16,%17,%18,%19,%20,%21,%22,%23,%24,%25,%26,%27,%28,%29,%30,%31,%32,%33,%34,%35,%36,%37,%38,%39,%40,%41,%42,%43,%44,%45,%46,%47,%48,%49,%50,%51,%52,%53,%54,%55,%56,%57,%58,%59,%60,%61,%62,%63}, {%64,%65,%66,%67}, %68, 0, 1, 1, %69;"
      : "=f"(d[0]),"=f"(d[1]),"=f"(d[2]),"=f"(d[3]),"=f"(d[4]),"=f"(d[5]),"=f"(d[6]),"=f"(d[7]),"=f"(d[8]),"=f"(d[9]),"=f"(d[10]),"=f"(d[11]),"=f"(d[12]),"=f"(d[13]),"=f"(d[14]),"=f"(d[15]),"=f"(d[16]),"=f"(d[17]),"=f"(d[18]),"=f"(d[19]),"=f"(d[20]),"=f"(d[21]),"=f"(d[22]),"=f"(d[23]),"=f"(d[24]),"=f"(d[25]),"=f"(d[26]),"=f"(d[27]),"=f"(d[28]),"=f"(d[29]),"=f"(d[30]),"=f"(d[31]),"=f"(d[32]),"=f"(d[33]),"=f"(d[34]),"=f"(d[35]),"=f"(d[36]),"=f"(d[37]),"=f"(d[38]),"=f"(d[39]),"=f"(d[40]),"=f"(d[41]),"=f"(d[42]),"=f"(d[43]),"=f"(d[44]),"=f"(d[45]),"=f"(d[46]),"=f"(d[47]),"=f"(d[48]),"=f"(d[49]),"=f"(d[50]),"=f"(d[51]),"=f"(d[52]),"=f"(d[53]),"=f"(d[54]),"=f"(d[55]),"=f"(d[56]),"=f"(d[57]),"=f"(d[58]),"=f"(d[59]),"=f"(d[60]),"=f"(d[61]),"=f"(d[62]),"=f"(d[63])
      : "r"(a[0]), "r"(a[1]), "r"(a[2]), "r"(a[3]), "l"(db), "n"(TB));
}
template<int TB, int SD, int TA = 0> __device__ __forceinline__ void wg_ss_n128(float* d, uint64_t da, uint64_t db) {
  if (SD)
    asm volatile("wgmma.mma_async.sync.aligned.m64n128k16.f32.bf16.bf16 {%0,%1,%2,%3,%4,%5,%6,%7,%8,%9,%10,%11,%12,%13,%14,%15,%16,%17,%18,%19,%20,%21,%22,%23,%24,%25,%26,%27,%28,%29,%30,%31,%32,%33,%34,%35,%36,%37,%38,%39,%40,%41,%42,%43,%44,%45,%46,%47,%48,%49,%50,%51,%52,%53,%54,%55,%56,%57,%58,%59,%60,%61,%62,%63}, %64, %65, 1, 1, 1, %67, %66;"
      : "+f"(d[0]),"+f"(d[1]),"+f"(d[2]),"+f"(d[3]),"+f"(d[4]),"+f"(d[5]),"+f"(d[6]),"+f"(d[7]),"+f"(d[8]),"+f"(d[9]),"+f"(d[10]),"+f"(d[11]),"+f"(d[12]),"+f"(d[13]),"+f"(d[14]),"+f"(d[15]),"+f"(d[16]),"+f"(d[17]),"+f"(d[18]),"+f"(d[19]),"+f"(d[20]),"+f"(d[21]),"+f"(d[22]),"+f"(d[23]),"+f"(d[24]),"+f"(d[25]),"+f"(d[26]),"+f"(d[27]),"+f"(d[28]),"+f"(d[29]),"+f"(d[30]),"+f"(d[31]),"+f"(d[32]),"+f"(d[33]),"+f"(d[34]),"+f"(d[35]),"+f"(d[36]),"+f"(d[37]),"+f"(d[38]),"+f"(d[39]),"+f"(d[40]),"+f"(d[41]),"+f"(d[42]),"+f"(d[43]),"+f"(d[44]),"+f"(d[45]),"+f"(d[46]),"+f"(d[47]),"+f"(d[48]),"+f"(d[49]),"+f"(d[50]),"+f"(d[51]),"+f"(d[52]),"+f"(d[53]),"+f"(d[54]),"+f"(d[55]),"+f"(d[56]),"+f"(d[57]),"+f"(d[58]),"+f"(d[59]),"+f"(d[60]),"+f"(d[61]),"+f"(d[62]),"+f"(d[63])
      : "l"(da), "l"(db), "n"(TB), "n"(TA));
  else
    asm volatile("wgmma.mma_async.sync.aligned.m64n128k16.f32.bf16.bf16 {%0,%1,%2,%3,%4,%5,%6,%7,%8,%9,%10,%11,%12,%13,%14,%15,%16,%17,%18,%19,%20,%21,%22,%23,%24,%25,%26,%27,%28,%29,%30,%31,%32,%33,%34,%35,%36,%37,%38,%39,%40,%41,%42,%43,%44,%45,%46,%47,%48,%49,%50,%51,%52,%53,%54,%55,%56,%57,%58,%59,%60,%61,%62,%63}, %64, %65, 0, 1, 1, %67, %66;"
      : "=f"(d[0]),"=f"(d[1]),"=f"(d[2]),"=f"(d[3]),"=f"(d[4]),"=f"(d[5]),"=f"(d[6]),"=f"(d[7]),"=f"(d[8]),"=f"(d[9]),"=f"(d[10]),"=f"(d[11]),"=f"(d[12]),"=f"(d[13]),"=f"(d[14]),"=f"(d[15]),"=f"(d[16]),"=f"(d[17]),"=f"(d[18]),"=f"(d[19]),"=f"(d[20]),"=f"(d[21]),"=f"(d[22]),"=f"(d[23]),"=f"(d[24]),"=f"(d[25]),"=f"(d[26]),"=f"(d[27]),"=f"(d[28]),"=f"(d[29]),"=f"(d[30]),"=f"(d[31]),"=f"(d[32]),"=f"(d[33]),"=f"(d[34]),"=f"(d[35]),"=f"(d[36]),"=f"(d[37]),"=f"(d[38]),"=f"(d[39]),"=f"(d[40]),"=f"(d[41]),"=f"(d[42]),"=f"(d[43]),"=f"(d[44]),"=f"(d[45]),"=f"(d[46]),"=f"(d[47]),"=f"(d[48]),"=f"(d[49]),"=f"(d[50]),"=f"(d[51]),"=f"(d[52]),"=f"(d[53]),"=f"(d[54]),"=f"(d[55]),"=f"(d[56]),"=f"(d[57]),"=f"(d[58]),"=f"(d[59]),"=f"(d[60]),"=f"(d[61]),"=f"(d[62]),"=f"(d[63])
      : "l"(da), "l"(db), "n"(TB), "n"(TA));
}

__device__ __forceinline__ void trap() { asm volatile("trap;"); }
__device__ __forceinline__ void wg_fence() { asm volatile("wgmma.fence.sync.aligned;" ::: "memory"); }
__device__ __forceinline__ void wg_commit() { asm volatile("wgmma.commit_group.sync.aligned;" ::: "memory"); }
template <int N> __device__ __forceinline__ void wg_wait() { asm volatile("wgmma.wait_group.sync.aligned %0;" ::"n"(N) : "memory"); }
template <int N> __device__ __forceinline__ void pin(float* r) {
#pragma unroll
  for (int i = 0; i < N; i++) asm volatile("" : "+f"(r[i])::"memory");
}
template <int N> __device__ __forceinline__ void clear(float* r) {
#pragma unroll
  for (int i = 0; i < N; i++) r[i] = 0.f;
  pin<N>(r);
}
template <int N> __device__ __forceinline__ void pin(uint32_t* r) {
#pragma unroll
  for (int i = 0; i < N; i++) asm volatile("" : "+r"(r[i])::"memory");
}
__host__ __device__ __forceinline__ constexpr uint64_t mkdesc(uint32_t addr, uint32_t lbo, uint32_t sbo, uint32_t swz) {
  return (uint64_t)((addr & 0x3FFFF) >> 4) | ((uint64_t)(lbo >> 4) << 16) | ((uint64_t)(sbo >> 4) << 32) | ((uint64_t)swz << 62);
}
__device__ __forceinline__ void mbar_init(uint32_t b, int c) { asm volatile("mbarrier.init.shared::cta.b64 [%0], %1;" ::"r"(b), "r"(c) : "memory"); }
__device__ __forceinline__ void mbar_expect(uint32_t b, int n) { asm volatile("mbarrier.arrive.expect_tx.shared::cta.b64 _, [%0], %1;" ::"r"(b), "r"(n) : "memory"); }
__device__ __forceinline__ void mbar_arrive(uint32_t b) { asm volatile("mbarrier.arrive.shared::cta.b64 _, [%0];" ::"r"(b) : "memory"); }
__device__ __forceinline__ bool mbar_try(uint32_t b, uint32_t ph) {
  uint32_t ok;
  asm volatile("{.reg .pred p; mbarrier.try_wait.parity.shared::cta.b64 p, [%1], %2; selp.u32 %0, 1, 0, p;}" : "=r"(ok) : "r"(b), "r"(ph) : "memory");
  return ok;
}
__device__ __forceinline__ void mbar_wait(uint32_t b, uint32_t ph) {
  if (mbar_try(b, ph)) return;
#pragma unroll 1
  for (int i = 0; i < (1 << 16); i++) {
    uint32_t ok;
    asm volatile("{.reg .pred p; mbarrier.try_wait.parity.shared::cta.b64 p, [%1], %2, 20000; selp.u32 %0, 1, 0, p;}" : "=r"(ok) : "r"(b), "r"(ph) : "memory");
    if (ok) return;
  }
  trap();
}
__device__ __forceinline__ void bulk_load(uint32_t dst, const void* src, int bytes, uint32_t bar) {
  asm volatile("cp.async.bulk.shared::cluster.global.mbarrier::complete_tx::bytes [%0], [%1], %2, [%3];" ::"r"(dst), "l"(src), "r"(bytes), "r"(bar) : "memory");
}
__device__ __forceinline__ void tma_load(uint32_t dst, const CUtensorMap* m, int c0, int c1, uint32_t bar) {
  asm volatile("cp.async.bulk.tensor.2d.shared::cluster.global.mbarrier::complete_tx::bytes [%0], [%1, {%2, %3}], [%4];" ::"r"(dst), "l"(m), "r"(c0), "r"(c1), "r"(bar) : "memory");
}
__device__ __forceinline__ void tma_prefetch(const CUtensorMap* m, int c0, int c1) {
  asm volatile("cp.async.bulk.prefetch.tensor.2d.L2.global [%0, {%1, %2}];" ::"l"(m), "r"(c0), "r"(c1) : "memory");
}
__device__ __forceinline__ bool elect() {
  uint32_t r;
  asm volatile("{.reg .pred p; elect.sync _|p, 0xffffffff; selp.u32 %0, 1, 0, p;}" : "=r"(r));
  return r;
}
__device__ __forceinline__ void bar_sync(int id, int n) { asm volatile("bar.sync %0, %1;" ::"r"(id), "r"(n) : "memory"); }
__device__ __forceinline__ void bar_arrive(int id, int n) { asm volatile("bar.arrive %0, %1;" ::"r"(id), "r"(n) : "memory"); }
__device__ __forceinline__ uint4 ldsm4(uint32_t a) {
  uint4 r;
  asm volatile("ldmatrix.sync.aligned.m8n8.x4.shared.b16 {%0, %1, %2, %3}, [%4];" : "=r"(r.x), "=r"(r.y), "=r"(r.z), "=r"(r.w) : "r"(a) : "memory");
  return r;
}
__device__ __forceinline__ void flag_add(int f, uint32_t n = 1) { asm volatile("red.release.gpu.global.add.u32 [%0], %1;" ::"l"(gFlag + f * 32), "r"(n) : "memory"); }
__device__ __forceinline__ void flag_wait(int f, uint32_t target, uint32_t ns) {
#pragma unroll 1
  for (int i = 0; i < (1 << 22); i++) {
    uint32_t v;
    asm volatile("ld.acquire.gpu.global.u32 %0, [%1];" : "=r"(v) : "l"(gFlag + f * 32) : "memory");
    if ((int)(v - target) >= 0) { asm volatile("fence.proxy.async.global;" ::: "memory"); return; }
    __nanosleep(ns);
  }
  trap();
}
__device__ __forceinline__ float ex2(float x) { float y; asm("ex2.approx.ftz.f32 %0, %1;" : "=f"(y) : "f"(x)); return y; }
__device__ __forceinline__ float rcp(float x) { float y; asm("rcp.approx.ftz.f32 %0, %1;" : "=f"(y) : "f"(x)); return y; }
__device__ __forceinline__ uint32_t packbf(float lo, float hi) { uint32_t d; asm("cvt.rn.bf16x2.f32 %0, %1, %2;" : "=r"(d) : "f"(hi), "f"(lo)); return d; }
__device__ __forceinline__ float bfr(float x) { return __bfloat162float(__float2bfloat16(x)); }
__device__ __forceinline__ uint32_t hmul(uint32_t a, uint32_t b) { uint32_t d; asm("mul.rn.bf16x2 %0, %1, %2;" : "=r"(d) : "r"(a), "r"(b)); return d; }
__device__ __forceinline__ uint32_t hadd(uint32_t a, uint32_t b) { uint32_t d; asm("add.rn.bf16x2 %0, %1, %2;" : "=r"(d) : "r"(a), "r"(b)); return d; }
__device__ __forceinline__ uint32_t hsub(uint32_t a, uint32_t b) { uint32_t d; asm("sub.rn.bf16x2 %0, %1, %2;" : "=r"(d) : "r"(a), "r"(b)); return d; }
__device__ __forceinline__ void hmma(float* c, const uint4& a, uint32_t b0, uint32_t b1) {
  asm("mma.sync.aligned.m16n8k16.row.col.f32.bf16.bf16.f32 {%0,%1,%2,%3},{%4,%5,%6,%7},{%8,%9},{%0,%1,%2,%3};"
      : "+f"(c[0]), "+f"(c[1]), "+f"(c[2]), "+f"(c[3]) : "r"(a.x), "r"(a.y), "r"(a.z), "r"(a.w), "r"(b0), "r"(b1));
}
constexpr float LOG2E = 1.4426950408889634f;

__device__ __forceinline__ uint32_t exp_poly(float lo, float hi, uint32_t half2) {
  uint32_t u, mh, p;
  asm("cvt.pack.sat.s16.s32 %0, %1, %2;" : "=r"(u) : "r"(__float_as_uint(hi)), "r"(__float_as_uint(lo)));
  asm("lop3.b32 %0, %1, 0x007F007F, %2, 0xEA;" : "=r"(mh) : "r"(u), "r"(half2));
  asm("fma.rn.bf16x2 %0, %1, %2, %3;" : "=r"(p) : "r"(u), "r"(mh), "r"(u & 0xFF80FF80u));
  return p;
}
__device__ __forceinline__ void softmax64(float* s, uint32_t* p, uint32_t half2) {
  pin<32>(s);
#pragma unroll
  for (int i = 0; i < 16; i++) p[i] = ((POLYMASK >> (i >> 1)) & 1) ? exp_poly(s[2 * i], s[2 * i + 1], half2) : packbf(ex2(s[2 * i]), ex2(s[2 * i + 1]));
  pin<16>(p);
}
__device__ __forceinline__ uint2 shift_frag(float rowmax) {
  const float y = (40.f * 0x1p-142f - rowmax) * 0x1p71f;
  const float r1 = y - __uint_as_float(__float_as_uint(y) & 0xFFFF0000u);
  const float r2 = r1 - __uint_as_float(__float_as_uint(r1) & 0xFFFF0000u);
  return make_uint2(__byte_perm(__float_as_uint(y), __float_as_uint(r1), 0x7632), __float_as_uint(r2) >> 16);
}
__device__ __forceinline__ float tanh_(float x) { float y; asm("tanh.approx.f32 %0, %1;" : "=f"(y) : "f"(x)); return y; }
__device__ __forceinline__ float silu_half(float h) { return fmaf(h, tanh_(h), h); }

__device__ __forceinline__ uint2 combine(uint2 x, uint32_t sa, uint32_t ga, uint32_t sb, uint32_t gb, int t) {
  const uint32_t ya = hmul(sa, ga), yb = hmul(sb, gb);
  const uint32_t e = __shfl_xor_sync(~0u, (t & 1) ? ya : yb, 1);
  return make_uint2(hadd(x.x, (t & 1) ? e : ya), hadd(x.y, (t & 1) ? yb : e));
}

template <bool V> struct Flag { static constexpr bool value = V; };
struct Tile { int kind, c0, c1; };
__device__ __forceinline__ Tile tile_of(int cg, int t) {
  const int c2 = cg >> 1;
  Tile r;
  if (cg & 1) {
    if (t == 0) { r.kind = 1; r.c0 = c2 * 128; r.c1 = r.c0 + 64; }
    else { r.kind = 2; r.c0 = r.c1 = (7 * c2 + 2 + t) * 64; }
  } else {
    if (t < 2) { r.kind = 0; r.c0 = 512 + c2 * 128 + t * 64; r.c1 = r.c0 + 512; }
    else { r.kind = 2; r.c0 = r.c1 = (7 * c2 + t - 2) * 64; }
  }
  return r;
}

constexpr uint32_t SB = 1024;
constexpr uint64_t VS = (uint64_t)(32 - (32LL << 16));
constexpr uint64_t dV0 = mkdesc(SB + SM_A + 4096, SM_ONES - SM_A - 4096, 256, 3);
constexpr uint32_t CH = (uint32_t)(16 * VS), HAND = 16, TAKE = 32, HELP = 64, EXACT = 128, LAST = 256;
__host__ __device__ constexpr uint64_t segs4(uint64_t a, uint64_t b, uint64_t c, uint64_t d) { return a | b << 16 | c << 32 | d << 48; }
constexpr uint64_t SEG1 = segs4(2 << 9 | HAND | 8, 5 << 9 | HAND | 9, 3 << 9, 4 << 9 | (NHC ? HELP : 0) | LAST);
constexpr uint64_t SEG2 = segs4(0 << 9 | 4, 2 << 9 | TAKE | 6, 1 << 9 | LAST, 0), SEG3 = segs4(6 << 9 | 5, 5 << 9 | TAKE | 7, 7 << 9 | LAST, 0);
constexpr uint32_t RNG1 = (15 - SPLIT2) << 4 | (15 - SPLIT5) << 12 | 15 << 20 | (uint32_t)(15 - NHC) << 28;
constexpr uint32_t RNG2 = 0xF0F0F0 | (16 - SPLIT2) << 8, RNG3 = 0xF0F0F0 | (16 - SPLIT5) << 8;

__global__ void __launch_bounds__(NTHREADS, 1)
fused_kernel(const bf16* __restrict__ x, bf16* __restrict__ out, uint64_t zero64, const __grid_constant__ CUtensorMap mX,
             const __grid_constant__ CUtensorMap mQKV, const __grid_constant__ CUtensorMap mW1, const __grid_constant__ CUtensorMap mW3,
             const __grid_constant__ CUtensorMap mW2, const __grid_constant__ CUtensorMap mWO) {
  const uint32_t zero = (uint32_t)zero64;
  extern __shared__ __align__(1024) uint8_t smem[];
  constexpr uint32_t sb = SB;
  if ((uint32_t)__cvta_generic_to_shared(smem) != sb) trap();
  const int tid = threadIdx.x, lane = tid & 31, g = lane >> 2, t = lane & 3;
  const int warp = __shfl_sync(~0u, tid >> 5, 0), wg = warp >> 2, w = warp & 3;
  const int b = blockIdx.x;
  const int rb = (b >> 5) * 4 + (b & 3), cg = (b >> 2) & 7;
  const int head = b >> 2, qb = b & 3;
  const int cb = b & 7;
  const int rEarly = (b >> 5) * 8 + ((0x6052 >> ((b >> 1) & 12)) & 7);

  if (wg < 4) TSTAMP(wg, 0);
  constexpr int HBYTES = NHC * 8192, HRES = 204800 / (HBYTES ? HBYTES : 1) < 8 ? 204800 / (HBYTES ? HBYTES : 1) : 8;
  if (warp == 0 && b < 128) {
    if (elect()) {
#pragma unroll
      for (int j = 0; j < 8; j++) mbar_init(sb + B_X + 8 * j, 1);
      asm volatile("fence.mbarrier_init.release.cluster;" ::: "memory");
#pragma unroll
      for (int j = 0; j < 8; j++) {
        mbar_expect(sb + B_X + 8 * j, 16384);
        tma_load(sb + SM_A + j * 16384, &mX, j * 64, rb * 128, sb + B_X + 8 * j);
      }
    }
    __syncwarp();
  }
  if (wg == 4) {
    asm volatile("setmaxnreg.dec.sync.aligned.u32 32;");
    if (b >= 128) {
      const int h0 = (b - 128) * 8;
      auto load_head = [&](int i) {
        if (elect()) {
          const uint8_t* src = gQKV + (uint32_t)((h0 + i) * HS);
          mbar_expect(sb + B_X + 8 * i, HBYTES + 1024);
          bulk_load(sb + 204800 + i * 1024, src, 1024, sb + B_X + 8 * i);
          bulk_load(sb + (i % HRES) * HBYTES, src + 131072 - HBYTES, HBYTES, sb + B_X + 8 * i);
        }
      };
      if (w == 0) {
        if (elect()) {
#pragma unroll
          for (int i = 0; i < 16; i++) mbar_init(sb + B_X + 8 * i, i < 8 ? 1 : 16);
          asm volatile("fence.mbarrier_init.release.cluster;" ::: "memory");
        }
        __syncwarp();
        bar_arrive(2, 544);
        uint32_t epoch;
        asm volatile("ld.relaxed.gpu.global.u32 %0, [%1];" : "=r"(epoch) : "l"(gFlag + (F_P + h0 * 4) * 32) : "memory");
#pragma unroll 1
        for (int i = 0; i < HRES; i++) {
          if ((i & 3) == 0) flag_wait(F_QKV + (h0 + i) / 4, (epoch + 1) * 32, 200);
          load_head(i);
        }
      }
#pragma unroll 1
      for (int i = 0; i < 8; i++) {
        bar_sync(4 + w, 160);
        if (lane == 0) flag_add(F_P + (h0 + i) * 4 + w);
        __syncwarp();
        if (w == 0 && i + HRES < 8) {
          mbar_wait(sb + B_X + 64 + 8 * i, 0);
          load_head(i + HRES);
        }
      }
      return;
    }
    auto read_epoch = [&]() {
      uint32_t e;
      asm volatile("ld.relaxed.gpu.global.u32 %0, [%1];" : "=r"(e) : "l"(gFlag + F_O * 32) : "memory");
      return (e >> 5) + 1;
    };
    uint32_t epoch = 0;
    if (w == 0) {
      if (elect()) {
#pragma unroll
        for (uint32_t a = B_FULL1; a < SM_TOTAL; a += 8) mbar_init(sb + a, a < B_EMPTY1 ? 1 : a == B_SHIFT ? 12 : a < B_KV ? 8 : a == B_KV ? KV1 : a == B_KV + 8 ? 8 - KV1 : a < B_TAKEN ? 4 : 2);
        asm volatile("fence.mbarrier_init.release.cluster;" ::: "memory");
      }
      __syncwarp();
      bar_sync(2, 576);
      int slot = 0;
      uint32_t ph = 1;
#pragma unroll 1
      for (int tI = 0; tI < NT1; tI++) {
        const Tile tl = tile_of(cg, tI);
        const CUtensorMap *m0 = tl.kind == 2 ? &mW1 : &mQKV, *m1 = tl.kind == 2 ? &mW3 : &mQKV;
#pragma unroll 1
        for (int k = 0; k < 8; k++) {
          const uint32_t full = sb + B_FULL1 + 8 * ((tI & 1) * NSLOT + slot), dst = sb + SM_RING + slot * 16384;
          if (tI == 0 && k == NSLOT) epoch = read_epoch();
          if (tI == 0 && k == BFREE) mbar_wait(sb + B_X + 8 * BGATE, 0);
          mbar_wait(sb + B_EMPTY1 + 8 * slot, ph);
          if (elect()) {
            mbar_expect(full, 16384);
            tma_load(dst, m0, tl.c0, k * 64, full);
            tma_load(dst + 8192, m1, tl.c1, k * 64, full);
          }
          if (++slot == NSLOT) { slot = 0; ph ^= 1; }
        }
      }
      mbar_wait(sb + B_K0, 0);
      asm volatile("fence.proxy.async.global;" ::: "memory");
#pragma unroll 1
      for (int j = 0; j < 8; j++) {
        if (j >= 8 - NSLOT) {
          mbar_wait(sb + B_EMPTY1 + 8 * slot, ph);
          if (++slot == NSLOT) { slot = 0; ph ^= 1; }
        }
        if (elect()) {
          mbar_expect(sb + B_KV + (j < KV1 ? 0 : 8), 16384);
          bulk_load(sb + SM_A + j * 16384, gQKV + (size_t)head * HS + j * 16384, 16384, sb + B_KV + (j < KV1 ? 0 : 8));
        }
      }
    } else {
      auto publish_tile = [&](int tI) {
        const Tile tl = tile_of(cg, tI);
        bar_sync(tI == NT1 - 1 ? 12 : 14 + (tI & 1), 288);
        if (lane < (tl.kind ? 2 : 1)) flag_add(tl.kind == 2 ? F_H + (pair_slot(rb * 2 + lane) >> 1) : F_QKV + ((tl.c0 >> 6) & 7) + lane);
        __syncwarp();
      };
      if (w < 3) {
        epoch = read_epoch();
#pragma unroll 1
        for (int tI = w - 1; tI < NT1 - 1; tI += 2) publish_tile(tI);
      } else {
        epoch = read_epoch();
        bar_sync(2, 576);
        mbar_wait(sb + B_X + 8 * PFS, 0);
        const int i = 2 * NSLOT + rb + lane * 16;
        if (i < 80) {
          const Tile tp = tile_of(cg, i >> 4);
          tma_prefetch((i & 1) ? (tp.kind == 2 ? &mW3 : &mQKV) : (tp.kind == 2 ? &mW1 : &mQKV), (i & 1) ? tp.c1 : tp.c0, ((i >> 1) & 7) * 64);
        }
        __syncwarp();
        bar_sync(11, 544);
        if (lane == 0) {
          asm volatile("cp.async.bulk.global.shared::cta.bulk_group [%0], [%1], 16384;" ::"l"(gD + (uint32_t)((rb * 8 + cg) * 16384)), "r"(sb + SM_A + cg * 16384) : "memory");
          asm volatile("cp.async.bulk.commit_group;" ::: "memory");
          asm volatile("cp.async.bulk.wait_group 0;" ::: "memory");
          asm volatile("fence.proxy.async.global;" ::: "memory");
          flag_add(F_D + rb);
        }
        __syncwarp();
        flag_wait(F_D + rb, epoch * 8, 300);
        flag_wait(F_QKV + (head >> 2), epoch * 32, 200);
        if (elect()) {
          mbar_expect(sb + B_K0, 1024);
          bulk_load(sb + SM_MERGE, gQKV + (size_t)head * HS, 1024, sb + B_K0);
        }
        __syncwarp();
        publish_tile(NT1 - 1);
      }
    }
    if (w < 3) {
      bar_sync(0, 96);
      asm volatile("fence.proxy.async.global;" ::: "memory");
      const uint32_t full = sb + B_FULL2 + 8 * w, dst = sb + SM_RING + w * 24576;
      int n = w, ph = 0;
#pragma unroll 1
      for (; n < NSH; n += 3, ph ^= 1) {
        if (elect()) {
          const int c = tile_of(cg, NT1).c0 + (n >> 4) * 64;
          mbar_expect(full, 24576);
          bulk_load(dst, gD + (uint32_t)(rb * 131072 + (n & 7) * 16384 + (n & 8) * 1024), 8192, full);
          tma_load(dst + 8192, &mW1, c, (n & 7) * 64, full);
          tma_load(dst + 16384, &mW3, c, (n & 7) * 64, full);
        }
        mbar_wait(sb + B_EMPTY2 + 8 * w, ph);
      }
      n -= NSH;
      flag_wait(F_H + (b >> 3), epoch * 56, 200);
      const uint8_t* hp = gH + (uint32_t)(((b >> 3) * 28 + n) * 16384);
#pragma unroll 1
      for (; n < 28; n += 3, ph ^= 1, hp += 3 * 16384) {
        if (elect()) {
          mbar_expect(full, 24576);
          tma_load(dst, &mW2, cb * 64, n * 64, full);
          bulk_load(dst + 8192, hp, 16384, full);
        }
        mbar_wait(sb + B_EMPTY2 + 8 * w, ph);
      }
      if (w == (NSH + 27) % 3) {
        if (elect()) {
          mbar_expect(sb + B_WO, 65536);
#pragma unroll
          for (int k = 0; k < 2; k++) tma_load(sb + SM_RING + k * 32768, &mWO, cb * 64, k * 256, sb + B_WO);
        }
        flag_wait(F_O + rEarly, epoch * 32, 300);
        if (lane == 0) mbar_arrive(sb + B_OE);
      }
    }
    if (NHC && w == (NSH + 29) % 3) {
      mbar_wait(sb + B_TAKEN, 0);
      flag_wait(F_P + b, epoch, 300);
      if (elect()) {
        mbar_expect(sb + B_HP, 5120);
        bulk_load(sb + SM_MERGE, gP + b * 5120, 5120, sb + B_HP);
      }
    }
    if (w == 3 || w == (NSH + 28) % 3) {
#pragma unroll 1
      for (int i = w == 3 ? 0 : 3; i < (w == 3 ? 3 : 4); i++) {
        const int r = (0x5260 >> (i * 4)) & 7;
        bar_sync(4 + i, 160);
        if (lane == 0) {
          if (i >= 2) mbar_arrive(sb + B_TAKEN);
          if (!*(volatile uint8_t*)(smem + SM_FAIL + r)) flag_add(F_O + qb * 8 + r);
        }
        __syncwarp();
      }
    }
    return;
  }
  asm volatile("setmaxnreg.inc.sync.aligned.u32 112;");

  float var;
  auto store_rstd = [&]() {
    float sd;
    asm("sqrt.approx.f32 %0, %1;" : "=f"(sd) : "f"(bfr(bfr(fmaxf(var, 0.f)) + 1e-5f)));
    if (t == (g >> 1)) ((float*)(smem + SM_RSTD))[warp * 8 + g] = rcp(bfr(sd));
  };
  const int wgp = wg ^ ((NT1 & 1) ? 0 : 2);
  {
    if (tid < 128) ((uint32_t*)(smem + SM_ONES))[tid] = 0x3F803F80u;
    if (tid < 14) ((uint32_t*)(smem + SM_ZERO))[tid] = 0;
    if (tid < 256) {
      const int n = tid >> 2, k = (tid & 3) * 4;
      const bool poly = (POLYMASK >> (n >> 3)) & 1;
      const float cm = -127.f + 0.5849625f - 0.0020f, chi = bfr(cm), clo = cm - chi, sc = poly ? 0x1p-71f : 0x1p71f;
      uint2 v = make_uint2(0, 0);
      if (k == 0) v = make_uint2(packbf(sc, sc), packbf(sc, 0.f));
      if (k == 8 && !poly) v.x = packbf(chi * sc, clo * sc);
      *(uint2*)(smem + SM_BIAS + n * 32 + (((k >> 3) ^ ((n >> 2) & 1)) << 4) + (k & 7) * 2) = v;
    }
    if (b >= 128) {
      asm volatile("fence.proxy.async.shared::cta;" ::: "memory");
      bar_sync(2, 544);
      const uint32_t half2 = 0x3F003F00u + zero;
      const uint64_t dBias = mkdesc(sb + SM_BIAS, 16, 256, 3) ^ zero64;
#pragma unroll 1
      for (int i = 0; i < 8; i++) {
        const int hd = (b - 128) * 8 + i;
        mbar_wait(sb + B_X + 8 * i, 0);
        const uint32_t* qp = (const uint32_t*)(gQKV + (uint32_t)(hd * HS + 131072 + (wg * 512 + 256 + w * 16 + g) * 32)) + t;
        uint32_t q[4] = {__ldcg(qp), __ldcg(qp + 64), __ldcg(qp + 4), __ldcg(qp + 68)}, qa[4], p0[16], p1[16];
        float s[32], o[12];
        {
          float a[16];
          wg_fence();
          wg_rs_n32<0, 0>(a, q, mkdesc(sb + 204800, 16, 256, 3) + i * 64);
          wg_commit();
          wg_wait<0>();
          pin<16>(a);
#pragma unroll
          for (int j = 0; j < 2; j++) {
            float v = fmaxf(fmaxf(fmaxf(a[2 * j], a[2 * j + 1]), fmaxf(a[2 * j + 4], a[2 * j + 5])), fmaxf(fmaxf(a[2 * j + 8], a[2 * j + 9]), fmaxf(a[2 * j + 12], a[2 * j + 13])));
            v = fmaxf(v, __shfl_xor_sync(~0u, v, 1));
            v = fmaxf(v, __shfl_xor_sync(~0u, v, 2));
            const uint2 f = shift_frag(v);
            qa[j] = (t & 1) ? f.y : f.x;
            qa[2 + j] = 0x1C001C00u | (zero & q[j]);
          }
        }
        clear<12>(o);
        uint64_t c = dV0 + (uint64_t)((i % HRES) * NHC) * (16 * VS);
        wg_fence();
        wg_rs_n64<0, 0>(s, qa, dBias);
        wg_rs_n64<0, 1>(s, q, c - 256);
        wg_commit();
        wg_wait<0>();
#pragma unroll 1
        for (int n = 0; n < NHC; n++) {
          softmax64(s, p0, half2);
          wg_fence();
          wg_rs_n64<0, 2>(s, qa, dBias);
          wg_rs_n64<0, 1>(s, q, c - 128);
          wg_commit();
#pragma unroll
          for (int k = 0; k < 4; k++) wg_rs_n24<1, 1>(o, p0 + 4 * k, c + k * VS);
          wg_commit();
          wg_wait<1>();
          softmax64(s, p1, half2);
          wg_fence();
          wg_rs_n64<0, 2>(s, qa, dBias);
          wg_rs_n64<0, 1>(s, q, c + 256);
          wg_commit();
#pragma unroll
          for (int k = 0; k < 4; k++) wg_rs_n24<1, 1>(o, p1 + 4 * k, c + (4 + k) * VS);
          wg_commit();
          c += 16 * VS;
          wg_wait<1>();
        }
        wg_wait<0>();
        pin<12>(o);
        if (lane == 0) mbar_arrive(sb + B_X + 64 + 8 * i);
        uint8_t* mp = gP + (uint32_t)((hd * 4 + wg) * 5120);
        *(float4*)(mp + (tid & 127) * 16) = make_float4(o[0], o[1], o[2], o[3]);
        *(float4*)(mp + 2048 + (tid & 127) * 16) = make_float4(o[4], o[5], o[6], o[7]);
        *(float2*)(mp + 4096 + (tid & 127) * 8) = make_float2(o[8], o[10]);
        bar_sync(4 + wg, 160);
      }
      return;
    }
    gO[((qb * 8 + ((0x7431 >> (wg * 4)) & 7)) * 32 + head) * 128 + (tid & 127)] = make_uint4(~0u, ~0u, ~0u, ~0u);
    float cs[4] = {0.f, 0.f, 0.f, 0.f}, ca[4] = {0.f, 0.f, 0.f, 0.f}, cb[4] = {0.f, 0.f, 0.f, 0.f};
    const int row = warp * 8 + g;
    const uint8_t* xs = smem + SM_A + row * 128;
    const int xo0 = (((4 * (g & 1) + t) ^ g) << 4), xo1 = xo0 ^ 64;
    bar_sync(2, 576);
    uint4 xl[4];
#pragma unroll
    for (int j = 0; j < 16; j++) {
      if ((j & 1) == 0) mbar_wait(sb + B_X + 4 * j, 0);
      if (j == 0 && wg >= 2) TSTAMP(wg, 6);
      if (j == 14 && wg >= 2) TSTAMP(wg, 7);
      const uint4 xv = *(const uint4*)(xs + (j >> 1) * 16384 + ((j & 1) ? xo1 : xo0));
      hmma(cs, xv, 0x3F803F80u, 0x3F803F80u);
      if (j < 16 - XL) {
        hmma(ca, xv, xv.x, xv.z);
        hmma(cb, xv, xv.y, xv.w);
      } else {
        xl[j - (16 - XL)] = xv;
      }
    }
    const float mean = (cs[0] + cs[2]) * (1.f / DM);
    if (t == 0) ((uint32_t*)(smem + SM_MEAN))[row] = packbf(mean, mean);
    if (wgp >= 2) bar_arrive(1, 512);
#pragma unroll
    for (int j = 0; j < XL; j++) {
      hmma(ca, xl[j], xl[j].x, xl[j].z);
      hmma(cb, xl[j], xl[j].y, xl[j].w);
    }
    if (wgp < 2) bar_sync(1, 512);
    var = ((g & 1) ? ca[1] + cb[3] : ca[0] + cb[2]) * (1.f / DM) - mean * mean;
    if (wgp >= 2) {
      store_rstd();
      asm volatile("fence.proxy.async.shared::cta;" ::: "memory");
      bar_arrive(10, 512);
    }
  }
  TSTAMP(wg, 1);
  const int pair = wgp >> 1, half = wg & 1;

  const uint8_t* qbase = gQKV + (uint32_t)(head * HS + 131072 + (qb * 512 + w * 16 + g) * 32 + t * 4);
  auto load_q = [&](uint32_t* q, int rbl) {
    const uint32_t* qp = (const uint32_t*)(qbase + rbl * 2048);
    q[0] = __ldcg(qp); q[1] = __ldcg(qp + 64); q[2] = __ldcg(qp + 4); q[3] = __ldcg(qp + 68);
  };
  uint32_t q4[16];
  auto store_h = [&](const float* acc, int hf, int slab, float r0, float r1) {
    const int ps = pair_slot(rb * 2 + hf);
    uint32_t* hp = (uint32_t*)(gH + (uint32_t)(((ps >> 1) * 28 + slab) * 16384 + (ps & 1) * 1024 + w * 256)) + lane;
#pragma unroll
    for (int j = 0; j < 8; j++) {
#pragma unroll
      for (int r = 0; r < 2; r++) {
        const float rs = r ? r1 : r0, rh = 0.5f * rs;
        const float h0 = silu_half(acc[4 * j + 2 * r] * rh) * (acc[32 + 4 * j + 2 * r] * rs);
        const float h1 = silu_half(acc[4 * j + 2 * r + 1] * rh) * (acc[33 + 4 * j + 2 * r] * rs);
        hp[j * 512 + r * 32] = packbf(h0, h1);
      }
    }
  };
  {
    const uint64_t dA0 = (mkdesc(sb + SM_A, 16, 1024, 1) ^ zero64) + half * 512, dB0 = mkdesc(sb + SM_RING, 8192, 1024, 1) ^ zero64;
    const bool lead = elect();
#pragma unroll 1
    for (int tI = pair; tI < NT1; tI += 2) {
      float acc[64];
      const uint32_t par = (uint32_t)(PARITY1 >> (tI * 8)), slots = (uint32_t)(0x432104321043210ull >> (((tI * 3) % NSLOT) * 4));
      if (tI == 0) {
        const uint32_t m0 = ((const uint32_t*)(smem + SM_MEAN))[half * 64 + w * 16 + g], m1 = ((const uint32_t*)(smem + SM_MEAN))[half * 64 + w * 16 + g + 8];
        const uint32_t xa = sb + SM_A + (half * 64 + w * 16 + (lane & 15)) * 128 + (((lane >> 4) ^ (lane & 7)) << 4);
        uint4 v0 = ldsm4(xa), v1 = ldsm4(xa ^ 32);
        mbar_wait(sb + B_FULL1, 0);
#pragma unroll
        for (int j = 0; j < 32; j++) {
          const int k = j >> 2;
          const uint32_t a[4] = {hsub(v0.x, m0), hsub(v0.y, m1), hsub(v0.z, m0), hsub(v0.w, m1)};
          asm volatile("stmatrix.sync.aligned.m8n8.x4.shared.b16 [%0], {%1, %2, %3, %4};" ::"r"((xa ^ ((j & 3) << 5)) + k * 16384), "r"(a[0]), "r"(a[1]), "r"(a[2]), "r"(a[3]) : "memory");
          wg_fence();
          if (j == 0) wg_rs_n128<1, 0>(acc, a, dB0); else wg_rs_n128<1, 1>(acc, a, dB0 + (k % NSLOT) * 1024 + (j & 3) * 128);
          wg_commit();
          if (j == FJ) asm volatile("fence.proxy.async.shared::cta;" ::: "memory");
          if (j == 2) store_rstd();
          if (j == HANDJ) bar_arrive(13, 512);
          if (j == 31) {
            if (FJ != 31) asm volatile("fence.proxy.async.shared::cta;" ::: "memory");
            bar_arrive(11, 544);
          }
          if ((j & 3) == 3 && j < 31) mbar_wait(sb + B_FULL1 + 8 * ((k + 1) % NSLOT), (k + 1) / NSLOT);
          if (j > 1) wg_wait<2>();
          if (j > 1 && (j & 3) == 1 && lead) mbar_arrive(sb + B_EMPTY1 + 8 * ((k + NSLOT - 1) % NSLOT));
          v0 = v1;
          if (j < 30) v1 = ldsm4((xa ^ (((j + 2) & 3) << 5)) + ((j + 2) >> 2) * 16384);
        }
        wg_wait<0>();
        if (lead) mbar_arrive(sb + B_EMPTY1 + 8 * (7 % NSLOT));
        bar_sync(10, 512);
        q4[0] = q4[1] = q4[2] = q4[3] = 0;
      } else {
      bar_sync(pair ? 13 : 3, 512);
#pragma unroll
      for (int k = 0; k < 8; k++) {
        const uint32_t slot = (slots >> (4 * k)) & 7;
        if (tI == TDBG && half == 0) TSTAMP(4, k);
        mbar_wait(sb + B_FULL1 + 8 * NSLOT * pair + 8 * slot, par >> k);
        if (tI == TDBG && half == 0) TSTAMP(4, 8 + k);
        const uint64_t dA = dA0 + k * 1024, dB = dB0 + slot * 1024;
        wg_fence();
        if (k == 0) wg_ss_n128<1, 0>(acc, dA, dB); else wg_ss_n128<1, 1>(acc, dA, dB);
        wg_ss_n128<1, 1>(acc, dA + 2, dB + 128);
        wg_ss_n128<1, 1>(acc, dA + 4, dB + 256);
        wg_ss_n128<1, 1>(acc, dA + 6, dB + 384);
        wg_commit();
        if (k == 7 && tI < NT1 - 1) bar_arrive(pair ? 3 : 13, 512);
        if (k == 4 && tI == 1) bar_sync(11, 544);
        if (k == 6 && tI == NT1 - 1) {
          mbar_wait(sb + B_K0, 0);
          load_q(q4, 2);
        }
        if (k > 0) {
          wg_wait<1>();
          if (lead) mbar_arrive(sb + B_EMPTY1 + 8 * ((slots >> (4 * k - 4)) & 7));
        }
      }
      wg_wait<0>();
      if (lead) mbar_arrive(sb + B_EMPTY1 + 8 * (slots >> 28));
      }
      pin<64>(acc);
      TSTAMP(wg, 2 + (tI >> 1) * 2);
      const Tile tl = tile_of(cg, tI);
      const int lrow = half * 64 + w * 16 + g;
      const float r0 = ((const float*)(smem + SM_RSTD))[lrow], r1 = ((const float*)(smem + SM_RSTD))[lrow + 8];
      if (tl.kind == 2) {
        store_h(acc, half, tl.c0 >> 6, r0, r1);
      } else {
        const bool isq = tl.kind == 1;
        uint8_t* p0 = gQKV + (uint32_t)(((tl.c0 >> 6) & 7) * 4 * HS + lrow * 32 + (isq ? 131072 + rb * 4096 + t * 8 : rb * 8192 + ((t * 8) ^ ((g & 4) << 2))));
        uint8_t* p1 = p0 + (isq ? 4 * HS : 4096);
        constexpr float QS = 0.25f * LOG2E * 0x1p-71f;
        const float k0 = ((POLYMASK >> (2 * w)) & 1) ? 0x1p-71f : 0x1p71f, k1 = ((POLYMASK >> (2 * w + 1)) & 1) ? 0x1p-71f : 0x1p71f;
        const float sc[4] = {r0 * (isq ? QS : k0), r1 * (isq ? QS : k1), r0 * (isq ? QS : 1.f), r1 * (isq ? QS : 1.f)};
#pragma unroll
        for (int i = 0; i < 16; i++) {
          const float* a = acc + (i >> 1) * 8 + 2 * (i & 1);
          const float f = sc[(i >> 3) * 2 + (i & 1)];
          *(uint2*)((i < 8 ? p0 : p1) + ((i >> 1) & 3) * HS + (i & 1) * 256) = make_uint2(packbf(a[0] * f, a[1] * f), packbf(a[4] * f, a[5] * f));
          if (PACE && (i & (PACEN - 1)) == PACEN - 1 && i < 15) __nanosleep(PACE);
        }
      }
      bar_arrive(tI == NT1 - 1 ? 12 : 14 + pair, 288);
      TSTAMP(wg, 3 + (tI >> 1) * 2);
    }
  }

  if (wg > 0) {
    if (wg >= 2) {
      mbar_wait(sb + B_K0, 0);
#pragma unroll
      for (int i = 0; i < 4; i++) load_q(q4 + 4 * i, (half * 6) ^ i);
      float s[64];
      wg_fence();
#pragma unroll
      for (int i = 0; i < 4; i++) wg_rs_n32<0, 0>(s + 16 * i, q4 + 4 * i, mkdesc(sb + SM_MERGE, 16, 256, 3));
      wg_commit();
      wg_wait<0>();
      pin<64>(s);
      static_assert((POLYMASK & 15) == 15, "the first 32 keys share one scale");
      float m[8];
#pragma unroll
      for (int i = 0; i < 8; i++) {
        const float* a = s + 16 * (i >> 1) + 2 * (i & 1);
        m[i] = fmaxf(fmaxf(fmaxf(a[0], a[1]), fmaxf(a[4], a[5])), fmaxf(fmaxf(a[8], a[9]), fmaxf(a[12], a[13])));
      }
#pragma unroll
      for (int i = 0; i < 4; i++) m[i] = fmaxf((t & 2) ? m[i + 4] : m[i], __shfl_xor_sync(~0u, (t & 2) ? m[i] : m[i + 4], 2));
#pragma unroll
      for (int i = 0; i < 2; i++) m[i] = fmaxf((t & 1) ? m[i + 2] : m[i], __shfl_xor_sync(~0u, (t & 1) ? m[i] : m[i + 2], 1));
      const uint2 f0 = shift_frag(m[0]), f1 = shift_frag(m[1]);
      ((uint4*)(smem + SM_SHIFT))[((half * 6) ^ t) * 32 + w * 8 + g] = make_uint4(f0.x, f1.x, f0.y, f1.y);
      __syncwarp();
      if (lane == 0) mbar_arrive(sb + B_SHIFT);
      TSTAMP(wg, 15);
    }
    const uint32_t half2 = 0x3F003F00u + zero;
    const uint64_t dBias = mkdesc(sb + SM_BIAS, 16, 256, 3) ^ zero64;
    uint32_t qa[4];
    qa[2] = 0x1C001C00u | (zero & q4[0]);
    qa[3] = 0x1C001C00u | (zero & q4[1]);
    auto keep = [&](uint32_t v) { return __shfl_sync(~0u, v, lane); };
    const uint32_t qkeep = keep(head * HS + 131072 + (qb * 512 + w * 16 + g) * 32 + t * 4), okeep = keep(((qb * 256 + head) * 128 + w * 32 + g * 4) * 16 + t * 8);
    const uint32_t skeep = keep(sb + SM_SHIFT + (w * 8 + g) * 16 + (t & 1) * 8);
    uint32_t mkeep = keep(sb + SM_MERGE + (wg == 3 ? 6144 : 0) + (tid & 127) * 48);
    auto load_shift = [&](uint32_t row512) { asm volatile("ld.shared.v2.u32 {%0, %1}, [%2];" : "=r"(qa[0]), "=r"(qa[1]) : "r"(skeep + row512) : "memory"); };
    auto load_qk = [&](uint32_t* q, uint32_t row512) {
      const uint32_t* qp = (const uint32_t*)(gQKV + (qkeep + row512 * 4));
      q[0] = __ldcg(qp); q[1] = __ldcg(qp + 64); q[2] = __ldcg(qp + 4); q[3] = __ldcg(qp + 68);
    };
    uint64_t segs = wg == 1 ? SEG1 : wg == 2 ? SEG2 : SEG3;
    uint32_t rng = wg == 1 ? RNG1 : wg == 2 ? RNG2 : RNG3, first = (uint32_t)dV0 - CH;
    uint32_t mine = wg == 1 ? 0x18 : wg == 2 ? 0x07 : 0xE0;
    uint32_t q[4] = {q4[0], q4[1], q4[2], q4[3]}, p0[16], p1[16];
    float s[32], o[12];
    clear<12>(o);
    if (wg == 1) mbar_wait(sb + B_SHIFT, 0);
    load_shift((uint32_t)segs & 0xE00);
    mbar_wait(sb + B_KV, 0);
    uint32_t cend = (uint32_t)dV0 + (wg == 1 ? 1 : 2 * KV1 - 2) * CH;
    TSTAMP(wg, 8);
    wg_fence();
    wg_rs_n64<0, 0>(s, qa, dBias);
    wg_rs_n64<0, 1>(s, q, dV0 - 256);
    wg_commit();
    wg_wait<0>();
#pragma unroll 1
    while (true) {
      const uint32_t cur = (uint32_t)segs, nrow = (cur >> 16) & 0xE00, last = (uint32_t)dV0 - CH + ((rng >> 4) & 15) * CH;
      uint64_t c = (dV0 & 0xFFFFFFFF00000000ull) | first;
      if (!cend) cend = last;
      segs >>= 16;
      rng >>= 8;
      first = (uint32_t)dV0 - CH + (rng & 15) * CH;
      auto next_chunk = [&]() {
        uint32_t lo;
        asm volatile("{.reg .b32 hi; mov.b64 {%1, hi}, %0; add.u32 %1, %1, %2; mov.b64 %0, {%1, hi};}" : "+l"(c), "=r"(lo) : "n"(CH));
        return lo;
      };
      uint32_t qn[4];
      load_qk(qn, nrow);
      auto first_half = [&](auto last) {
        CSTAMP();
        softmax64(s, p0, half2);
        wg_fence();
        wg_rs_n64<0, 2>(s, qa, dBias);
        wg_rs_n64<0, 1>(s, q, c - 128);
        wg_commit();
#pragma unroll
        for (int k = 0; k < 4; k++) wg_rs_n24<1, 1>(o, p0 + 4 * k, c + k * VS);
        wg_commit();
        wg_wait<last.value ? 0 : 1>();
        softmax64(s, p1, half2);
      };
      auto second_half = [&](uint64_t dKnext) {
        wg_fence();
        wg_rs_n64<0, 2>(s, qa, dBias);
        wg_rs_n64<0, 1>(s, q, dKnext);
        wg_commit();
#pragma unroll
        for (int k = 0; k < 4; k++) wg_rs_n24<1, 1>(o, p1 + 4 * k, c + (4 + k) * VS);
        wg_commit();
      };
#pragma unroll 1
      while (true) {
        uint32_t lo;
#pragma unroll 1
        do {
          lo = next_chunk();
          first_half(Flag<false>());
          second_half(c + 256);
          wg_wait<1>();
        } while (lo != cend);
        if (cend == last) break;
        cend = last;
        mbar_wait(sb + B_KV + 8, 0);
      }
      if (TAILA && (cur & HELP)) bar_arrive(3, 256);
      next_chunk();
      first_half(Flag<true>());
      load_shift(nrow);
#pragma unroll
      for (int i = 0; i < 4; i++) q[i] = qn[i] ^ zero;
      pin<4>(q);
      second_half((dV0 & 0xFFFFFFFF00000000ull) | (first + CH - 256));
      const bool take = cur & (TAKE << 16);
      if (take) bar_sync(6 + wg, 256);
      const uint32_t ia = take ? mkeep : sb + SM_ZERO;
      wg_wait<0>();
      pin<12>(o);
      if (cur & HAND) {
#pragma unroll
        for (int i = 0; i < 3; i++) asm volatile("st.shared.v4.f32 [%0], {%1, %2, %3, %4};" ::"r"(mkeep + i * 16), "f"(o[4 * i]), "f"(o[4 * i + 1]), "f"(o[4 * i + 2]), "f"(o[4 * i + 3]) : "memory");
        mkeep += 6144;
        bar_arrive(cur & 15, 256);
      } else {
        if (cur & HELP) {
          mbar_wait(sb + B_HP, 0);
          const float4 u = ((const float4*)(smem + SM_MERGE))[tid & 127], v = ((const float4*)(smem + SM_MERGE + 2048))[tid & 127];
          const float2 l = ((const float2*)(smem + SM_MERGE + 4096))[tid & 127];
          o[0] += u.x; o[1] += u.y; o[2] += u.z; o[3] += u.w; o[4] += v.x; o[5] += v.y; o[6] += v.z; o[7] += v.w;
          o[8] += l.x; o[10] += l.y;
        }
        const float i0 = rcp(o[8]), i1 = rcp(o[10]);
        asm volatile("{.reg .pred p, e; .reg .b64 u, v; .reg .b16 one;"
                     " setp.ne.u32 e, %8, 0; setp.lt.f32 p, %5, 0f71800000; setp.lt.and.f32 p, %6, 0f71800000, p; or.pred p, p, e;"
                     " mov.b64 u, {%1, %2}; mov.b64 v, {%3, %4}; mov.b16 one, 1;"
                     " @p st.relaxed.gpu.global.b64 [%0], u; @p st.relaxed.gpu.global.b64 [%0 + 32], v; @!p st.shared.b8 [%7], one;}"
                     ::"l"((uint8_t*)gO + (okeep + (cur & 0xE00) * 128)), "r"(packbf(o[0] * i0, o[1] * i0)), "r"(packbf(o[2] * i1, o[3] * i1)), "r"(packbf(o[4] * i0, o[5] * i0)),
                       "r"(packbf(o[6] * i1, o[7] * i1)), "f"(o[8]), "f"(o[10]), "r"(sb + SM_FAIL + ((cur >> 9) & 7)), "r"(cur & EXACT) : "memory");
        if (cur & 15) bar_arrive(cur & 15, 160);
      }
#pragma unroll
      for (int i = 0; i < 3; i++) asm volatile("ld.shared.v4.f32 {%0, %1, %2, %3}, [%4];" : "+f"(o[4 * i]), "+f"(o[4 * i + 1]), "+f"(o[4 * i + 2]), "+f"(o[4 * i + 3]) : "r"(ia + i * 16) : "memory");
      TSTAMP(wg, (cur & LAST) ? 11 : 10);
      if (cur & LAST) {
        bar_sync(9 + wg, 128);
        if ((cur & EXACT) && ((0x65 >> (cur >> 9)) & 1) && (tid & 127) == 0) flag_add(F_O + qb * 8 + (cur >> 9));
        const uint32_t fail = __ballot_sync(~0u, *(volatile uint8_t*)(smem + SM_FAIL + (lane & 7))) & mine;
        if (!fail) break;
        {
          const int r = __ffs(fail) - 1;
          mine &= ~(1u << r);
          segs = r << 9 | EXACT | LAST;
          rng = 0xF0;
          load_qk(q, r << 9);
          float m[4] = {-INFINITY, -INFINITY, -INFINITY, -INFINITY};
#pragma unroll 1
          for (int i = 0; i < 32 + (int)zero; i++) {
            wg_fence();
            wg_rs_n64<0, 2>(s, q, dV0 - 256 + (i >> 1) * 512 + (i & 1) * 128);
            wg_commit();
            wg_wait<0>();
            pin<32>(s);
#pragma unroll
            for (int j = 0; j < 16; j++) {
              float& mm = m[(((POLYMASK >> (j >> 1)) & 1) ? 0 : 2) + (j & 1)];
              mm = fmaxf(mm, fmaxf(s[2 * j], s[2 * j + 1]));
            }
          }
#pragma unroll
          for (int j = 0; j < 2; j++) {
            float v = fmaxf(m[j], (m[2 + j] * 0x1p-71f) * 0x1p-71f);
            v = fmaxf(v, __shfl_xor_sync(~0u, v, 1));
            v = fmaxf(v, __shfl_xor_sync(~0u, v, 2));
            const uint2 f = shift_frag(v);
            qa[j] = (t & 1) ? f.y : f.x;
          }
          wg_fence();
          wg_rs_n64<0, 2>(s, qa, dBias);
          wg_rs_n64<0, 1>(s, q, dV0 - 256);
          wg_commit();
          wg_wait<0>();
        }
      }
      cend = 0;
    }
  } else {
    const uint64_t dB0 = mkdesc(sb + SM_RING, 8192, 1024, 1) ^ zero64;
    const bool lead = elect();
    {
      const float* rs = (const float*)(smem + SM_RSTD) + w * 16 + g;
      const float rA0 = rs[0], rA1 = rs[8], rB0 = rs[64], rB1 = rs[72];
      __syncwarp();
      if (lead) mbar_arrive(sb + B_SHIFT);
      const uint64_t dA0 = mkdesc(sb + SM_RING, 16, 1024, 1) ^ zero64;
      uint32_t slot = 0, ph = 0;
#pragma unroll 1
      for (int p = 0; p < NSH / 8; p++) {
        float acc[64];
#pragma unroll
        for (int k = 0; k < 8; k++) {
          mbar_wait(sb + B_FULL2 + 8 * slot, ph);
          CSTAMP();
          const uint64_t dA = dA0 + slot * 1536, dB = dB0 + 512 + slot * 1536;
          wg_fence();
          if (k == 0) wg_ss_n128<1, 0>(acc, dA, dB); else wg_ss_n128<1, 1>(acc, dA, dB);
          wg_ss_n128<1, 1>(acc, dA + 2, dB + 128);
          wg_ss_n128<1, 1>(acc, dA + 4, dB + 256);
          wg_ss_n128<1, 1>(acc, dA + 6, dB + 384);
          wg_commit();
          wg_wait<0>();
          if (lead) mbar_arrive(sb + B_EMPTY2 + 8 * slot);
          if (++slot == 3) { slot = 0; ph ^= 1; }
        }
        pin<64>(acc);
        store_h(acc, p & 1, (tile_of(cg, NT1).c0 >> 6) + (p >> 1), (p & 1) ? rB0 : rA0, (p & 1) ? rB1 : rA1);
      }
      bar_sync(2, 128);
      if (NSH && tid < 2) flag_add(F_H + (pair_slot(rb * 2 + tid) >> 1), 5 - NT1);
      __syncwarp();
      TSTAMP(wg, 15);
    }
    {
      uint64_t dW = dB0, dH = mkdesc(sb + SM_RING + 8192, 2048, 128, 0) ^ zero64;
      float acc[64];
      auto stage = [&](auto first, const int slot, uint32_t ph) {
        mbar_wait(sb + B_FULL2 + 8 * slot, ph);
        CSTAMP();
        wg_fence();
        wg_ss_n128<0, !first.value, 1>(acc, dW + slot * 1536, dH + slot * 1536);
#pragma unroll
        for (int k = 1; k < 4; k++) wg_ss_n128<0, 1, 1>(acc, dW + slot * 1536 + k * 128, dH + slot * 1536 + k * 256);
        wg_commit();
        wg_wait<0>();
        if (lead) mbar_arrive(sb + B_EMPTY2 + 8 * slot);
      };
      stage(Flag<true>(), NSH % 3, NSH / 3);
#pragma unroll 1
      for (int n = 0; n < 9; n++) {
        dW += zero64; dH += zero64;
        stage(Flag<false>(), (NSH + 1) % 3, (NSH + 1) / 3 + n);
        stage(Flag<false>(), (NSH + 2) % 3, (NSH + 2) / 3 + n);
        stage(Flag<false>(), NSH % 3, NSH / 3 + n + 1);
      }
      pin<64>(acc);
      bar_sync(2, 128);
      auto silu2 = [&](float f0, float f1) { return packbf(silu_half(0.5f * f0), silu_half(0.5f * f1)); };
#pragma unroll
      for (int i = 0; i < 8; i++) {
        const float* a = acc + 8 * i;
        asm volatile("stmatrix.sync.aligned.m8n8.x4.trans.shared.b16 [%0], {%1, %2, %3, %4};" ::"r"(sb + SM_GATE + (i >> 2) * 8192 + w * 2048 + (i & 3) * 512 + lane * 16),
                     "r"(silu2(a[0], a[1])), "r"(silu2(a[4], a[5])), "r"(silu2(a[2], a[3])), "r"(silu2(a[6], a[7])) : "memory");
      }
      bar_sync(2, 128);
    }
    TSTAMP(wg, 8);
    {
      mbar_wait(sb + B_WO, 0);
      mbar_wait(sb + B_OE, 0);
      TSTAMP(wg, 11);
      const uint4* op = gO + rEarly * 32 * 128 + tid;
      float acc[32];
      clear<32>(acc);
      uint64_t dB = dB0;
#pragma unroll 1
      for (int n = 0; n < 4; n++, op += 1024, dB += 1024) {
        uint32_t a[32];
#pragma unroll
        for (int i = 0; i < 8; i++) {
          const uint4 v = __ldcg(op + i * 128);
          a[4 * i] = v.x; a[4 * i + 1] = v.y; a[4 * i + 2] = v.z; a[4 * i + 3] = v.w;
        }
        wg_fence();
#pragma unroll
        for (int i = 0; i < 8; i++) wg_rs_n64<1, 1>(acc, a + 4 * i, dB + i * 128);
        wg_commit();
        wg_wait<0>();
      }
      pin<32>(acc);
      TSTAMP(wg, 9);
      const uint32_t off = (rEarly * 64 + w * 16 + g) * DM + cb * 64 + (t & 1) * 8 + (t & 2) * 2;
      const bf16* xp = x + off;
      bf16* yp = out + off;
#pragma unroll
      for (int i = 0; i < 4; i++) {
        const uint4 gt = ldsm4(sb + SM_GATE + i * 2048 + tid * 16);
        const float* c = acc + 8 * i;
        *(uint2*)(yp + i * 16) = combine(__ldg((const uint2*)(xp + i * 16)), packbf(c[0], c[1]), gt.x, packbf(c[4], c[5]), gt.z, t);
        *(uint2*)(yp + i * 16 + 8 * DM) = combine(__ldg((const uint2*)(xp + i * 16 + 8 * DM)), packbf(c[2], c[3]), gt.y, packbf(c[6], c[7]), gt.w, t);
      }
      TSTAMP(wg, 10);
    }
  }

  if (wg < 2) {
    int tid, b;
    asm volatile("mov.u32 %0, %%tid.x;" : "=r"(tid));
    asm volatile("mov.u32 %0, %%ctaid.x;" : "=r"(b));
    const int g = (tid >> 2) & 7, t = tid & 3, w = (tid >> 5) & 3;
    const int rLate = (b >> 5) * 8 + ((0x3741 >> ((b >> 1) & 12)) & 7);
    const uint32_t off = (rLate * 64 + w * 16 + g) * DM + (b & 7) * 64 + wg * 32 + (t & 1) * 8 + (t & 2) * 2;
    const uint4* op = gO + (rLate * 32 + wg * 16) * 128 + (tid & 127);
    if (wg == 0) bar_sync(3, 256);
    else { mbar_wait(sb + B_OE, 0); mbar_wait(sb + B_WO, 0); }
    uint32_t a[64];
#pragma unroll
    for (int i = 0; i < 16; i++)
      asm volatile("{.reg .b64 u, v; ld.relaxed.gpu.global.v2.b64 {u, v}, [%4]; mov.b64 {%0, %1}, u; mov.b64 {%2, %3}, v;}"
                   : "=r"(a[4 * i]), "=r"(a[4 * i + 1]), "=r"(a[4 * i + 2]), "=r"(a[4 * i + 3]) : "l"(op + i * 128) : "memory");
    mbar_wait(sb + B_TAKEN, 0);
#pragma unroll 1
    for (int it = 0; it < (1 << 20); it++) {
      uint32_t bad = 0;
#pragma unroll
      for (int i = 0; i < 16; i++) {
        const uint32_t m = max(a[4 * i], a[4 * i + 2]);
        bad = max(bad, m);
        asm volatile("{.reg .pred p; .reg .b64 u, v; setp.eq.u32 p, %5, 0xffffffff; mov.b64 u, {%0, %1}; mov.b64 v, {%2, %3};"
                     " @p ld.relaxed.gpu.global.v2.b64 {u, v}, [%4]; mov.b64 {%0, %1}, u; mov.b64 {%2, %3}, v;}"
                     : "+r"(a[4 * i]), "+r"(a[4 * i + 1]), "+r"(a[4 * i + 2]), "+r"(a[4 * i + 3]) : "l"(op + i * 128), "r"(m) : "memory");
      }
      if (!__any_sync(~0u, bad == ~0u)) break;
      if (TSLEEP) __nanosleep(TSLEEP);
    }
    TSTAMP(wg, 14);
    float acc[16];
    const uint64_t dB = (mkdesc(sb + SM_RING, 8192, 1024, 1) ^ zero64) + wg * 2048;
    float4* ex0 = (float4*)(smem + (wg ? SM_MERGE : SM_GATE)) + (tid & 127);
    const float4* ex1 = (const float4*)(smem + (wg ? SM_GATE : SM_MERGE)) + (tid & 127);
    uint2 xr[4];
    uint4 gt0, gt1;
#pragma unroll
    for (int pass = 0; pass < 2; pass++) {
      const uint64_t dBp = dB + ((wg ^ pass ^ 1) << 2);
      wg_fence();
      if (pass == 0) wg_rs_n32<1, 0>(acc, a, dBp); else wg_rs_n32<1, 2>(acc, a, dBp);
#pragma unroll
      for (int i = 1; i < 16; i++) wg_rs_n32<1, 1>(acc, a + 4 * i, dBp + i * 128);
      wg_commit();
      if (pass == 0) {
#pragma unroll
        for (int i = 0; i < 4; i++) xr[i] = __ldg((const uint2*)(x + off + (i & 1) * 8 * DM + (i >> 1) * 16));
      } else {
        bar_sync(1, 256);
        gt0 = ldsm4(sb + SM_GATE + 8192 + (wg * 2) * 2048 + (tid & 127) * 16);
        gt1 = ldsm4(sb + SM_GATE + 8192 + (wg * 2 + 1) * 2048 + (tid & 127) * 16);
      }
      wg_wait<0>();
      pin<16>(acc);
      if (pass == 0) {
#pragma unroll
        for (int i = 0; i < 4; i++) ex0[i * 128] = make_float4(acc[4 * i], acc[4 * i + 1], acc[4 * i + 2], acc[4 * i + 3]);
      }
    }
    TSTAMP(wg, 13);
#pragma unroll
    for (int j = 0; j < 2; j++) {
      const uint4 gt = TAILE ? (j ? gt1 : gt0) : ldsm4(sb + SM_GATE + 8192 + (wg * 2 + j) * 2048 + (tid & 127) * 16);
      const float4 u = ex1[2 * j * 128], v = ex1[(2 * j + 1) * 128];
      const float* c = acc + 8 * j;
      *(uint2*)(out + off + j * 16) = combine(xr[2 * j], packbf(c[0] + u.x, c[1] + u.y), gt.x, packbf(c[4] + v.x, c[5] + v.y), gt.z, t);
      *(uint2*)(out + off + j * 16 + 8 * DM) = combine(xr[2 * j + 1], packbf(c[2] + u.z, c[3] + u.w), gt.y, packbf(c[6] + v.z, c[7] + v.w), gt.w, t);
    }
    TSTAMP(wg, 12);
  }
}

typedef CUresult (*EncodeFn)(CUtensorMap*, CUtensorMapDataType, cuuint32_t, void*, const cuuint64_t*, const cuuint64_t*, const cuuint32_t*,
                             const cuuint32_t*, CUtensorMapInterleave, CUtensorMapSwizzle, CUtensorMapL2promotion, CUtensorMapFloatOOBfill);

void make_map(EncodeFn enc, CUtensorMap* m, void* p, int rows, int cols, int boxrows = 64) {
  const cuuint64_t dims[2] = {(cuuint64_t)cols, (cuuint64_t)rows}, strides[1] = {(cuuint64_t)cols * 2};
  const cuuint32_t box[2] = {64, (cuuint32_t)boxrows}, es[2] = {1, 1};
  enc(m, CU_TENSOR_MAP_DATA_TYPE_BFLOAT16, 2, p, dims, strides, box, es, CU_TENSOR_MAP_INTERLEAVE_NONE, CU_TENSOR_MAP_SWIZZLE_128B,
      CU_TENSOR_MAP_L2_PROMOTION_L2_128B, CU_TENSOR_MAP_FLOAT_OOB_FILL_NONE);
}

}

extern "C" void kernel_launch(void* const* d_in, const int* in_sizes, int n_in, void* d_out, int out_size) {
  (void)in_sizes; (void)n_in; (void)out_size;
  void* fn = nullptr;
  cudaDriverEntryPointQueryResult qr;
  cudaGetDriverEntryPoint("cuTensorMapEncodeTiled", &fn, cudaEnableDefault, &qr);
  EncodeFn enc = (EncodeFn)fn;
  CUtensorMap mQKV, mW1, mW3, mW2, mWO, mX;
  make_map(enc, &mX, d_in[0], SEQ, DM, 128);
  make_map(enc, &mQKV, d_in[1], DM, 3 * DM);
  make_map(enc, &mWO, d_in[2], DM, DM, 256);
  make_map(enc, &mW1, d_in[4], DM, FF);
  make_map(enc, &mW3, d_in[5], DM, FF);
  make_map(enc, &mW2, d_in[6], FF, DM);
  cudaFuncSetAttribute(fused_kernel, cudaFuncAttributeMaxDynamicSharedMemorySize, SM_TOTAL);
  fused_kernel<<<NHC ? 132 : 128, NTHREADS, SM_TOTAL>>>((const bf16*)d_in[0], (bf16*)d_out, 0ull, mX, mQKV, mW1, mW3, mW2, mWO);
}
```
